```python
import torch

def _softmax(x, axis=-1):
    return torch.softmax(x, dim=axis)
def _gelu(x):
    return torch.nn.functional.gelu(x, approximate="tanh")
def _silu(x):
    return torch.nn.functional.silu(x)
def _sigmoid(x):
    return torch.sigmoid(x)
def _layernorm(x, axis=-1, eps=1e-5):
    m = x.mean(dim=axis, keepdim=True)
    v = x.var(dim=axis, keepdim=True, unbiased=False)
    return (x - m) / torch.sqrt(v + eps)
def _scatter_add(tgt, idx, src, axis=0):
    return tgt.clone().index_add_(axis, idx, src)
def _segment_sum(src, seg, n):
    out = torch.zeros((n,) + src.shape[1:], dtype=src.dtype)
    return out.index_add_(0, seg, src)
def _pad(x, pw):
    flat = tuple(v for pair in reversed(pw) for v in pair)
    return torch.nn.functional.pad(x, flat)

kernel_name = 'concat_heads__ssm_conv_h3__sliding_local_dilated__prompt'

def setup_inputs():

    _w = (lambda a: (lambda t: t.to(torch.bfloat16) if t.is_floating_point() else t)(torch.as_tensor(a)))
    def _A_setup():
        B, S, D = 1, 2048, 640
        ks = 4
        return {
            "q": _w((lambda *s: torch.randn(*s, dtype=torch.bfloat16) * 0.05)(B, S, D)),
            "k": _w((lambda *s: torch.randn(*s, dtype=torch.bfloat16) * 0.8)(B, S, D)),
            "v": _w((lambda *s: torch.randn(*s, dtype=torch.bfloat16) * 0.8)(B, S, D)),
            "shift_k": _w((lambda *s: torch.randn(*s, dtype=torch.bfloat16) * 0.8)(D, ks) * 0.5),
            "ssm_k": _w((lambda *s: torch.randn(*s, dtype=torch.bfloat16) * 3.2)(D, S) * (1.0 / S ** 0.5)),
            "ssm_D": _w((lambda *s: torch.randn(*s, dtype=torch.bfloat16) * 0.8)(D)),
        }
    _A_in = _A_setup()

    def _B_setup():
        B, S, D = 1, 2048, 640
        return {
            "x": _w((lambda *s: torch.randn(*s, dtype=torch.bfloat16) * 0.2)(B, S, D)),
            "wqkv": _w((lambda *s: torch.randn(*s, dtype=torch.bfloat16) * 0.2)(D, 3 * D)),
            "wo": _w((lambda *s: torch.randn(*s, dtype=torch.bfloat16) * 0.05)(D, D)),
        }
    _B_in = _B_setup()

    return {
        "A_q": _A_in["q"],
        "A_k": _A_in["k"],
        "A_v": _A_in["v"],
        "A_shift_k": _A_in["shift_k"],
        "A_ssm_k": _A_in["ssm_k"],
        "A_ssm_D": _A_in["ssm_D"],
        "B_x": _B_in["x"],
        "B_wqkv": _B_in["wqkv"],
        "B_wo": _B_in["wo"],
    }

def reference(A_q, A_k, A_v, A_shift_k, A_ssm_k, A_ssm_D, B_x, B_wqkv, B_wo):
    def _A_ref(q, k, v, shift_k, ssm_k, ssm_D):
        B, S, D = q.shape
        ks = shift_k.shape[-1]
        k_pad = _pad(k, ((0, 0), (ks - 1, 0), (0, 0)))
        k_shift = torch.zeros_like(k)
        for t in range(ks):
            k_shift = k_shift + k_pad[:, t:t + S, :] * shift_k[:, ks - 1 - t][None, None, :]
        kv = k_shift * v
        L = 2 * S
        kv_pad = _pad(kv, ((0, 0), (0, S), (0, 0)))
        kf_pad = _pad(ssm_k, ((0, 0), (0, S)))
        kv_f = (lambda x, axes=(-2,-1): torch.fft.rfft2(x.float(), dim=axes))(kv_pad[:, None, :, :], axes=(1, 2))
        kf_f = (lambda x, axes=(-2,-1): torch.fft.rfft2(x.float(), dim=axes))(kf_pad[:, None, :], axes=(1, 2))
        kf_f = (lambda x, *d: x.permute(*d))(kf_f, 1, 2, 0)
        y_f = kv_f * kf_f[None, :, :, :]
        y = (lambda x, s, axes=(-2,-1): torch.fft.irfft2(x, s=s, dim=axes).to(torch.bfloat16))(y_f, (1, L), axes=(1, 2))[:, 0, :S, :]
        y = y + kv * ssm_D[None, None, :]
        return q * y

    def _B_ref(x, wqkv, wo):
        B, S, D = x.shape
        H = 32; Dh = D // H
        W, dil = 8, 2
        qkv = (lambda x, *d: x.permute(*d))((x @ wqkv).reshape(B, S, 3, H, Dh), 2, 0, 3, 1, 4)
        q, k, v = qkv[0], qkv[1], qkv[2]
        scale = Dh ** -0.5
        pos = torch.arange(S)
        off = torch.arange(W) * dil
        idx = pos[:, None] - off[None, :]
        mask = idx >= 0
        idx_c = torch.where(mask, idx, 0).reshape(-1)
        kg = k[:, :, idx_c, :].reshape(B, H, S, W, Dh)
        vg = v[:, :, idx_c, :].reshape(B, H, S, W, Dh)
        logits = torch.einsum("bhsd,bhswd->bhsw", q, kg) * scale
        logits = torch.where(mask[None, None, :, :], logits, -1e9)
        attn = _softmax(logits, axis=-1)
        o = torch.einsum("bhsw,bhswd->bhsd", attn, vg)
        return (lambda x, *d: x.permute(*d))(o, 0, 2, 1, 3).reshape(B, S, D) @ wo

    a = _A_ref(A_q, A_k, A_v, A_shift_k, A_ssm_k, A_ssm_D)
    b = _B_ref(B_x, B_wqkv, B_wo)
    return torch.concatenate([a, b], axis=-1)
```

```cpp
#include <cuda_runtime.h>
#include <cuda_bf16.h>
#include <cuda.h>
#include <stdint.h>

typedef __nv_bfloat16 bf16;
typedef __nv_bfloat162 bf162;

__device__ __align__(1024) bf16 g_o[2048 * 640];
__device__ __align__(1024) bf16 g_xr[640 * 2048];
__device__ __align__(1024) bf16 g_y[640 * 2048];
__device__ __align__(1024) uint2 g_halo[128 * 640];
__device__ unsigned g_epoch;
constexpr int NCNT = 32 * 24;
__device__ __align__(128) unsigned g_cnt[NCNT];
#define CNT_PRE 0
#define CNT_EXIT 32
#define CNT_O(tt) (64 + 32 * (tt))
#define CNT_Y(c) (576 + 32 * (c))
#define CSTAMP(i)
#define STAMP(i)

constexpr int NSX = 4, NSW = 5;
constexpr int WR_OFF = NSX * 16384;
constexpr int WSL = 15360;
constexpr int KV_OFF = 0;
constexpr int KV_PITCH = 336;
constexpr int OST_OFF = 49152;
constexpr int ST2 = 28672;
constexpr int NS2 = 4;
constexpr int XCH_OFF = NS2 * ST2;
constexpr int CH_OFF = XCH_OFF + 32768;
constexpr int CH_SZ = 12544;
constexpr int HB_OFF = 128, HA_OFF = 4288, XR_OFF = 8384;
constexpr int KS_OFF = CH_OFF, VS_OFF = CH_OFF + 19 * 1280, SH_OFF = CH_OFF + 35 * 1280;
constexpr int QS_OFF = CH_OFF + 5 * CH_SZ;
constexpr int BAR_OFF = QS_OFF + 20480;
constexpr int SMEM_BYTES = BAR_OFF + 512 + 1024;
enum { B_FX = 0, B_EX = 4, B_FW = 8, B_EW = 13, B_FULL2 = 18, B_EMPTY2 = 22, B_XH = 26, B_YDONE = 31, B_SLAB = 36, B_QS = 37, B_OST = 38, B_COUNT = 39 };

__device__ __forceinline__ uint32_t s2u(const void* p) { return (uint32_t)__cvta_generic_to_shared(p); }
__device__ __forceinline__ void mbar_init(uint32_t a, int c) { asm volatile("mbarrier.init.shared.b64 [%0], %1;" ::"r"(a), "r"(c) : "memory"); }
__device__ __forceinline__ void mbar_expect(uint32_t a, uint32_t b) { asm volatile("mbarrier.arrive.expect_tx.shared.b64 _, [%0], %1;" ::"r"(a), "r"(b) : "memory"); }
__device__ __forceinline__ void mbar_arrive(uint32_t a) { asm volatile("mbarrier.arrive.shared.b64 _, [%0];" ::"r"(a) : "memory"); }
__device__ __forceinline__ void mbar_wait(uint32_t a, uint32_t ph) {
  for (int i = 0; i < (1 << 15); i++) {
    uint32_t ok;
    asm volatile("{\n.reg .pred p;\nmbarrier.try_wait.parity.shared.b64 p, [%1], %2;\nselp.u32 %0, 1, 0, p;\n}" : "=r"(ok) : "r"(a), "r"(ph) : "memory");
    if (ok) return;
  }
}
__device__ __forceinline__ void wait_ge(const unsigned* p, unsigned target) {
  for (int i = 0; i < (1 << 17); i++) {
    unsigned v;
    asm volatile("ld.acquire.gpu.global.u32 %0, [%1];" : "=r"(v) : "l"(p) : "memory");
    if (v >= target) return;
  }
}
__device__ __forceinline__ void red_release(unsigned* p, unsigned v) { asm volatile("red.release.gpu.global.add.u32 [%0], %1;" ::"l"(p), "r"(v) : "memory"); }
__device__ __forceinline__ void red_relaxed(unsigned* p, unsigned v) { asm volatile("red.relaxed.gpu.global.add.u32 [%0], %1;" ::"l"(p), "r"(v) : "memory"); }
__device__ __forceinline__ uint32_t movtrans(uint32_t a) { uint32_t r; asm volatile("movmatrix.sync.aligned.m8n8.trans.b16 %0, %1;" : "=r"(r) : "r"(a)); return r; }
__device__ __forceinline__ void fence_async_s() { asm volatile("fence.proxy.async.shared::cta;" ::: "memory"); }
__device__ __forceinline__ void fence_async_g() { asm volatile("fence.proxy.async.global;" ::: "memory"); }
__device__ __forceinline__ void bar_sync(int id, int n) { asm volatile("bar.sync %0, %1;" ::"r"(id), "r"(n) : "memory"); }
__device__ __forceinline__ void tma2(uint32_t dst, const CUtensorMap* m, int c0, int c1, uint32_t bar) {
  asm volatile("cp.async.bulk.tensor.2d.shared::cluster.global.mbarrier::complete_tx::bytes [%0], [%1, {%3, %4}], [%2];" ::"r"(dst), "l"(m), "r"(bar), "r"(c0), "r"(c1) : "memory");
}
__device__ __forceinline__ void tma3(uint32_t dst, const CUtensorMap* m, int c0, int c1, int c2, uint32_t bar) {
  asm volatile("cp.async.bulk.tensor.3d.shared::cluster.global.mbarrier::complete_tx::bytes [%0], [%1, {%3, %4, %5}], [%2];" ::"r"(dst), "l"(m), "r"(bar), "r"(c0), "r"(c1), "r"(c2) : "memory");
}
__device__ __forceinline__ void tma2mc(uint32_t dst, const CUtensorMap* m, int c0, int c1, uint32_t bar) {
  asm volatile("cp.async.bulk.tensor.2d.shared::cluster.global.mbarrier::complete_tx::bytes.multicast::cluster [%0], [%1, {%3, %4}], [%2], %5;" ::"r"(dst), "l"(m), "r"(bar), "r"(c0), "r"(c1), "h"((uint16_t)3) : "memory");
}
__device__ __forceinline__ void tma3mc(uint32_t dst, const CUtensorMap* m, int c0, int c1, int c2, uint32_t bar) {
  asm volatile("cp.async.bulk.tensor.3d.shared::cluster.global.mbarrier::complete_tx::bytes.multicast::cluster [%0], [%1, {%3, %4, %5}], [%2], %6;" ::"r"(dst), "l"(m), "r"(bar), "r"(c0), "r"(c1), "r"(c2), "h"((uint16_t)3) : "memory");
}
__device__ __forceinline__ void mbar_arrive_cl(uint32_t a, uint32_t rank) {
  asm volatile("{\n.reg .b32 r;\nmapa.shared::cluster.u32 r, %0, %1;\nmbarrier.arrive.shared::cluster.b64 _, [r];\n}" ::"r"(a), "r"(rank) : "memory");
}
__device__ __forceinline__ void tma2_st(const CUtensorMap* m, int c0, int c1, uint32_t src) {
  asm volatile("cp.async.bulk.tensor.2d.global.shared::cta.bulk_group [%0, {%2, %3}], [%1];" ::"l"(m), "r"(src), "r"(c0), "r"(c1) : "memory");
}
__device__ __forceinline__ void tma3_st(const CUtensorMap* m, int c0, int c1, int c2, uint32_t src) {
  asm volatile("cp.async.bulk.tensor.3d.global.shared::cta.bulk_group [%0, {%2, %3, %4}], [%1];" ::"l"(m), "r"(src), "r"(c0), "r"(c1), "r"(c2) : "memory");
}
__device__ __forceinline__ void bulk_ld(uint32_t dst, const void* src, uint32_t n, uint32_t bar) {
  asm volatile("cp.async.bulk.shared::cluster.global.mbarrier::complete_tx::bytes [%0], [%1], %2, [%3];" ::"r"(dst), "l"(src), "r"(n), "r"(bar) : "memory");
}
__device__ __forceinline__ void bulk_st(void* dst, uint32_t src, uint32_t n) {
  asm volatile("cp.async.bulk.global.shared::cta.bulk_group [%0], [%1], %2;" ::"l"(dst), "r"(src), "r"(n) : "memory");
}
__device__ __forceinline__ void l2_prefetch(const void* src, uint32_t n) { asm volatile("cp.async.bulk.prefetch.L2.global [%0], %1;" ::"l"(src), "r"(n) : "memory"); }
__device__ __forceinline__ void bulk_commit() { asm volatile("cp.async.bulk.commit_group;" ::: "memory"); }
__device__ __forceinline__ void bulk_wait0() { asm volatile("cp.async.bulk.wait_group 0;" ::: "memory"); }
#define WG_FENCE() asm volatile("wgmma.fence.sync.aligned;" ::: "memory")
#define WG_COMMIT() asm volatile("wgmma.commit_group.sync.aligned;" ::: "memory")
#define WG_WAIT(n) asm volatile("wgmma.wait_group.sync.aligned " #n ";" ::: "memory")
__device__ __forceinline__ uint64_t mkdesc(uint32_t addr, uint32_t lbo, uint32_t sbo, uint32_t lt) {
  return (uint64_t)((addr & 0x3FFFF) >> 4) | ((uint64_t)(lbo >> 4) << 16) | ((uint64_t)(sbo >> 4) << 32) | ((uint64_t)lt << 62);
}
__device__ __forceinline__ uint32_t pack2(float lo, float hi) { uint32_t r; asm("cvt.rn.bf16x2.f32 %0, %1, %2;" : "=r"(r) : "f"(hi), "f"(lo)); return r; }
__device__ __forceinline__ float lo2f(uint32_t p) { return __uint_as_float(p << 16); }
__device__ __forceinline__ float hi2f(uint32_t p) { return __uint_as_float(p & 0xFFFF0000u); }
__device__ __forceinline__ float ex2f(float x) { float r; asm("ex2.approx.ftz.f32 %0, %1;" : "=f"(r) : "f"(x)); return r; }
__device__ __forceinline__ float rcpf(float x) { float r; asm("rcp.approx.ftz.f32 %0, %1;" : "=f"(r) : "f"(x)); return r; }
__device__ __forceinline__ void stsm4(uint32_t a, uint32_t r0, uint32_t r1, uint32_t r2, uint32_t r3) {
  asm volatile("stmatrix.sync.aligned.m8n8.x4.shared.b16 [%0], {%1, %2, %3, %4};" ::"r"(a), "r"(r0), "r"(r1), "r"(r2), "r"(r3) : "memory");
}
__device__ __forceinline__ void ldsm4(uint32_t a, uint32_t& r0, uint32_t& r1, uint32_t& r2, uint32_t& r3) {
  asm volatile("ldmatrix.sync.aligned.m8n8.x4.shared.b16 {%0, %1, %2, %3}, [%4];" : "=r"(r0), "=r"(r1), "=r"(r2), "=r"(r3) : "r"(a) : "memory");
}
__device__ __forceinline__ void ldsm2(uint32_t a, uint32_t& r0, uint32_t& r1) {
  asm volatile("ldmatrix.sync.aligned.m8n8.x2.shared.b16 {%0, %1}, [%2];" : "=r"(r0), "=r"(r1) : "r"(a) : "memory");
}
__device__ __forceinline__ void ldsm4t(uint32_t a, uint32_t& r0, uint32_t& r1, uint32_t& r2, uint32_t& r3) {
  asm volatile("ldmatrix.sync.aligned.m8n8.x4.trans.shared.b16 {%0, %1, %2, %3}, [%4];" : "=r"(r0), "=r"(r1), "=r"(r2), "=r"(r3) : "r"(a) : "memory");
}
__device__ __forceinline__ void ldsm2t(uint32_t a, uint32_t& r0, uint32_t& r1) {
  asm volatile("ldmatrix.sync.aligned.m8n8.x2.trans.shared.b16 {%0, %1}, [%2];" : "=r"(r0), "=r"(r1) : "r"(a) : "memory");
}
__device__ __forceinline__ void mma16(float (&c)[4], uint32_t a0, uint32_t a1, uint32_t a2, uint32_t a3, uint32_t b0, uint32_t b1) {
  asm("mma.sync.aligned.m16n8k16.row.col.f32.bf16.bf16.f32 {%0,%1,%2,%3}, {%4,%5,%6,%7}, {%8,%9}, {%0,%1,%2,%3};"
               : "+f"(c[0]), "+f"(c[1]), "+f"(c[2]), "+f"(c[3]) : "r"(a0), "r"(a1), "r"(a2), "r"(a3), "r"(b0), "r"(b1));
}
__device__ __forceinline__ void mma8(float (&c)[4], uint32_t a0, uint32_t a1, uint32_t b0) {
  asm("mma.sync.aligned.m16n8k8.row.col.f32.bf16.bf16.f32 {%0,%1,%2,%3}, {%4,%5}, {%6}, {%0,%1,%2,%3};"
               : "+f"(c[0]), "+f"(c[1]), "+f"(c[2]), "+f"(c[3]) : "r"(a0), "r"(a1), "r"(b0));
}
__device__ __forceinline__ uint32_t lds32(uint32_t a) { uint32_t v; asm volatile("ld.shared.u32 %0, [%1];" : "=r"(v) : "r"(a) : "memory"); return v; }
__device__ __forceinline__ uint32_t lds16(uint32_t a) { uint16_t v; asm volatile("ld.shared.u16 %0, [%1];" : "=h"(v) : "r"(a) : "memory"); return v; }
__device__ __forceinline__ void sts16(uint32_t a, uint16_t v) { asm volatile("st.shared.u16 [%0], %1;" ::"r"(a), "h"(v) : "memory"); }
__device__ __forceinline__ void sts64f(uint32_t a, float x, float y) { asm volatile("st.shared.v2.f32 [%0], {%1, %2};" ::"r"(a), "f"(x), "f"(y) : "memory"); }
__device__ __forceinline__ float2 lds64f(uint32_t a) { float2 v; asm volatile("ld.shared.v2.f32 {%0, %1}, [%2];" : "=f"(v.x), "=f"(v.y) : "r"(a) : "memory"); return v; }
__device__ __forceinline__ uint32_t hmul2u(uint32_t a, uint32_t b) { uint32_t r; asm("mul.rn.bf16x2 %0, %1, %2;" : "=r"(r) : "r"(a), "r"(b)); return r; }
__device__ __forceinline__ uint32_t hadd2u(uint32_t a, uint32_t b) { uint32_t r; asm("add.rn.bf16x2 %0, %1, %2;" : "=r"(r) : "r"(a), "r"(b)); return r; }

__device__ __forceinline__ void wg192(float (&d)[96], uint64_t da, uint64_t db, int sc) {
  asm volatile("{\n.reg .pred p;\nsetp.ne.b32 p, %98, 0;\n"
    "wgmma.mma_async.sync.aligned.m64n192k16.f32.bf16.bf16 {%0, %1, %2, %3, %4, %5, %6, %7, %8, %9, %10, %11, %12, %13, %14, %15, %16, %17, %18, %19, %20, %21, %22, %23, %24, %25, %26, %27, %28, %29, %30, %31, %32, %33, %34, %35, %36, %37, %38, %39, %40, %41, %42, %43, %44, %45, %46, %47, %48, %49, %50, %51, %52, %53, %54, %55, %56, %57, %58, %59, %60, %61, %62, %63, %64, %65, %66, %67, %68, %69, %70, %71, %72, %73, %74, %75, %76, %77, %78, %79, %80, %81, %82, %83, %84, %85, %86, %87, %88, %89, %90, %91, %92, %93, %94, %95}, %96, %97, p, 1, 1, 0, 1;\n}"
    : "+f"(d[0]), "+f"(d[1]), "+f"(d[2]), "+f"(d[3]), "+f"(d[4]), "+f"(d[5]), "+f"(d[6]), "+f"(d[7]), "+f"(d[8]), "+f"(d[9]), "+f"(d[10]), "+f"(d[11]), "+f"(d[12]), "+f"(d[13]), "+f"(d[14]), "+f"(d[15]), "+f"(d[16]), "+f"(d[17]), "+f"(d[18]), "+f"(d[19]), "+f"(d[20]), "+f"(d[21]), "+f"(d[22]), "+f"(d[23]), "+f"(d[24]), "+f"(d[25]), "+f"(d[26]), "+f"(d[27]), "+f"(d[28]), "+f"(d[29]), "+f"(d[30]), "+f"(d[31]), "+f"(d[32]), "+f"(d[33]), "+f"(d[34]), "+f"(d[35]), "+f"(d[36]), "+f"(d[37]), "+f"(d[38]), "+f"(d[39]), "+f"(d[40]), "+f"(d[41]), "+f"(d[42]), "+f"(d[43]), "+f"(d[44]), "+f"(d[45]), "+f"(d[46]), "+f"(d[47]), "+f"(d[48]), "+f"(d[49]), "+f"(d[50]), "+f"(d[51]), "+f"(d[52]), "+f"(d[53]), "+f"(d[54]), "+f"(d[55]), "+f"(d[56]), "+f"(d[57]), "+f"(d[58]), "+f"(d[59]), "+f"(d[60]), "+f"(d[61]), "+f"(d[62]), "+f"(d[63]), "+f"(d[64]), "+f"(d[65]), "+f"(d[66]), "+f"(d[67]), "+f"(d[68]), "+f"(d[69]), "+f"(d[70]), "+f"(d[71]), "+f"(d[72]), "+f"(d[73]), "+f"(d[74]), "+f"(d[75]), "+f"(d[76]), "+f"(d[77]), "+f"(d[78]), "+f"(d[79]), "+f"(d[80]), "+f"(d[81]), "+f"(d[82]), "+f"(d[83]), "+f"(d[84]), "+f"(d[85]), "+f"(d[86]), "+f"(d[87]), "+f"(d[88]), "+f"(d[89]), "+f"(d[90]), "+f"(d[91]), "+f"(d[92]), "+f"(d[93]), "+f"(d[94]), "+f"(d[95])
    : "l"(da), "l"(db), "r"(sc));
}
__device__ __forceinline__ void wg48(float (&d)[24], uint64_t da, uint64_t db, int sc) {
  asm volatile("{\n.reg .pred p;\nsetp.ne.b32 p, %26, 0;\n"
    "wgmma.mma_async.sync.aligned.m64n48k16.f32.bf16.bf16 {%0, %1, %2, %3, %4, %5, %6, %7, %8, %9, %10, %11, %12, %13, %14, %15, %16, %17, %18, %19, %20, %21, %22, %23}, %24, %25, p, 1, 1, 0, 1;\n}"
    : "+f"(d[0]), "+f"(d[1]), "+f"(d[2]), "+f"(d[3]), "+f"(d[4]), "+f"(d[5]), "+f"(d[6]), "+f"(d[7]), "+f"(d[8]), "+f"(d[9]), "+f"(d[10]), "+f"(d[11]), "+f"(d[12]), "+f"(d[13]), "+f"(d[14]), "+f"(d[15]), "+f"(d[16]), "+f"(d[17]), "+f"(d[18]), "+f"(d[19]), "+f"(d[20]), "+f"(d[21]), "+f"(d[22]), "+f"(d[23])
    : "l"(da), "l"(db), "r"(sc));
}
__device__ __forceinline__ void wg80(float (&d)[40], uint64_t da, uint64_t db, int sc) {
  asm volatile("{\n.reg .pred p;\nsetp.ne.b32 p, %42, 0;\n"
    "wgmma.mma_async.sync.aligned.m64n80k16.f32.bf16.bf16 {%0, %1, %2, %3, %4, %5, %6, %7, %8, %9, %10, %11, %12, %13, %14, %15, %16, %17, %18, %19, %20, %21, %22, %23, %24, %25, %26, %27, %28, %29, %30, %31, %32, %33, %34, %35, %36, %37, %38, %39}, %40, %41, p, 1, 1, 0, 1;\n}"
    : "+f"(d[0]), "+f"(d[1]), "+f"(d[2]), "+f"(d[3]), "+f"(d[4]), "+f"(d[5]), "+f"(d[6]), "+f"(d[7]), "+f"(d[8]), "+f"(d[9]), "+f"(d[10]), "+f"(d[11]), "+f"(d[12]), "+f"(d[13]), "+f"(d[14]), "+f"(d[15]), "+f"(d[16]), "+f"(d[17]), "+f"(d[18]), "+f"(d[19]), "+f"(d[20]), "+f"(d[21]), "+f"(d[22]), "+f"(d[23]), "+f"(d[24]), "+f"(d[25]), "+f"(d[26]), "+f"(d[27]), "+f"(d[28]), "+f"(d[29]), "+f"(d[30]), "+f"(d[31]), "+f"(d[32]), "+f"(d[33]), "+f"(d[34]), "+f"(d[35]), "+f"(d[36]), "+f"(d[37]), "+f"(d[38]), "+f"(d[39])
    : "l"(da), "l"(db), "r"(sc));
}
__device__ __forceinline__ void cv32_0(float* d, const uint32_t* a, uint64_t db) {
  asm volatile("wgmma.mma_async.sync.aligned.m64n32k16.f32.bf16.bf16 {%0, %1, %2, %3, %4, %5, %6, %7, %8, %9, %10, %11, %12, %13, %14, %15}, {%16,%17,%18,%19}, %20, 0, 1, 1, 0;"
    : "=f"(d[0]), "=f"(d[1]), "=f"(d[2]), "=f"(d[3]), "=f"(d[4]), "=f"(d[5]), "=f"(d[6]), "=f"(d[7]), "=f"(d[8]), "=f"(d[9]), "=f"(d[10]), "=f"(d[11]), "=f"(d[12]), "=f"(d[13]), "=f"(d[14]), "=f"(d[15])
    : "r"(a[0]), "r"(a[1]), "r"(a[2]), "r"(a[3]), "l"(db));
}
__device__ __forceinline__ void cv32_1(float* d, const uint32_t* a, uint64_t db) {
  asm volatile("wgmma.mma_async.sync.aligned.m64n32k16.f32.bf16.bf16 {%0, %1, %2, %3, %4, %5, %6, %7, %8, %9, %10, %11, %12, %13, %14, %15}, {%16,%17,%18,%19}, %20, 1, 1, 1, 0;"
    : "+f"(d[0]), "+f"(d[1]), "+f"(d[2]), "+f"(d[3]), "+f"(d[4]), "+f"(d[5]), "+f"(d[6]), "+f"(d[7]), "+f"(d[8]), "+f"(d[9]), "+f"(d[10]), "+f"(d[11]), "+f"(d[12]), "+f"(d[13]), "+f"(d[14]), "+f"(d[15])
    : "r"(a[0]), "r"(a[1]), "r"(a[2]), "r"(a[3]), "l"(db));
}
__device__ __forceinline__ void cv16_1(float* d, const uint32_t* a, uint64_t db) {
  asm volatile("wgmma.mma_async.sync.aligned.m64n16k16.f32.bf16.bf16 {%0, %1, %2, %3, %4, %5, %6, %7}, {%8,%9,%10,%11}, %12, 1, 1, 1, 0;"
    : "+f"(d[0]), "+f"(d[1]), "+f"(d[2]), "+f"(d[3]), "+f"(d[4]), "+f"(d[5]), "+f"(d[6]), "+f"(d[7])
    : "r"(a[0]), "r"(a[1]), "r"(a[2]), "r"(a[3]), "l"(db));
}

template <int I0, int I1> __device__ __forceinline__ void conv_lda(uint32_t (&a)[64], uint32_t ab) {
#pragma unroll
  for (int i = I0; i < I1; i++) {
    a[4 * i] = lds32(ab + 256 * i); a[4 * i + 1] = lds32(ab + 128 + 256 * i); a[4 * i + 2] = lds32(ab + 16 + 256 * i); a[4 * i + 3] = lds32(ab + 144 + 256 * i);
  }
}
template <int S> __device__ __forceinline__ void conv_step(float (&d)[32], const uint32_t (&a)[64], uint64_t db) {
  cv32_0(&d[0], &a[0], db + 64 * S); cv32_0(&d[16], &a[0], db + 64 * S + 32);
#pragma unroll
  for (int i = 1; i < 16 - 4 * S; i++) {
    if (i < 15 - 4 * S) cv32_1(&d[0], &a[4 * i], db + 16 * i + 64 * S); else cv16_1(&d[0], &a[4 * i], db + 16 * i + 64 * S);
    if (i < 13 - 4 * S) cv32_1(&d[16], &a[4 * i], db + 16 * i + 64 * S + 32);
    if (i == 13 - 4 * S) cv16_1(&d[16], &a[4 * i], db + 16 * i + 64 * S + 32);
  }
  WG_COMMIT();
}
template <int S> __device__ __forceinline__ void conv_epi_a(const float (&d)[32], float (&ch)[2], float (&cr)[2], uint32_t xw, bool bw) {
  constexpr int H = (S & 1) * 2048;
  const float r0 = d[0] + d[6], r1 = d[1] + d[7];
  sts64f(xw + H + (bw ? 8 * 256 : 0), bw ? cr[0] : r0, bw ? cr[1] : r1);
  cr[0] = r0; cr[1] = r1;
#pragma unroll
  for (int q = 7; q > 0; q--) sts64f(xw + H + q * 256, d[4 * q] + (q == 7 ? ch[0] : d[4 * q + 6]), d[4 * q + 1] + (q == 7 ? ch[1] : d[4 * q + 7]));
  ch[0] = d[2]; ch[1] = d[3];
}
template <int S> __device__ __forceinline__ void conv_epi_b(uint32_t xr, uint32_t ys, uint32_t ks, uint32_t dd, int barid) {
  constexpr int H = (S & 1) * 2048;
  uint32_t kd[2];
#pragma unroll
  for (int q = 0; q < 2; q++) kd[q] = lds16(ks + 1024 * S + 128 * q - 16) | (lds16(ks + 1024 * S + 128 * q) << 16);
  bar_sync(barid, 128);
  float2 p[2][4];
#pragma unroll
  for (int q = 0; q < 2; q++)
#pragma unroll
    for (int w = 0; w < 4; w++) p[q][w] = lds64f(xr + H + w * 4096 + q * 256);
#pragma unroll
  for (int q = 0; q < 2; q++) {
    const float ya = (p[q][0].x + p[q][1].x) + (p[q][2].x + p[q][3].x), yb = (p[q][0].y + p[q][1].y) + (p[q][2].y + p[q][3].y);
    const uint32_t r = hadd2u(pack2(ya, yb), hmul2u(kd[q], dd));
    sts16(ys - 1024 * S - 128 * q + 16, (uint16_t)(r & 0xFFFF));
    sts16(ys - 1024 * S - 128 * q, (uint16_t)(r >> 16));
  }
}

#define EXIT_COUNT() do { if (atomicAdd(&g_cnt[CNT_EXIT], 1) == 128 * 6 - 1) { for (int _i = 0; _i < NCNT; _i += 32) g_cnt[_i] = 0; g_epoch = g_epoch + 1; } } while (0)

struct Params {
  const bf16 *q, *k, *v, *shift, *h, *dvec, *x, *wqkv, *wo;
  bf16* out;
};

__global__ void __cluster_dims__(2, 1, 1) __launch_bounds__(512, 1)
fused_kernel(const __grid_constant__ CUtensorMap tmX, const __grid_constant__ CUtensorMap tmW64, const __grid_constant__ CUtensorMap tmW16,
             const __grid_constant__ CUtensorMap tmWo, const __grid_constant__ CUtensorMap tmOld, const __grid_constant__ CUtensorMap tmOst,
             const __grid_constant__ CUtensorMap tmOut, const Params P) {
  extern __shared__ uint8_t smem_raw[];
  const uint32_t sb = (s2u(smem_raw) + 1023) & ~1023u;
  const uint32_t bars = sb + BAR_OFF;
  const int tid = threadIdx.x, warp = __shfl_sync(~0u, tid >> 5, 0), lane = tid & 31, wg = warp >> 2;
  const int b = blockIdx.x, rank = b & 1;
  const int tt = (b >> 5) * 4 + (b & 3), hg = ((b >> 4) & 1) * 4 + ((b >> 2) & 3), par = tt >> 3, rt = tt & 7, tid8 = tt * 8 + hg;
#define BAR(i) (bars + 8 * (i))
  constexpr int STW = 0;
  if (warp == 12) {
    if (lane == 0) {
      STAMP(0);
      for (int i = 0; i < NSX; i++) { mbar_init(BAR(B_FX + i), 1); mbar_init(BAR(B_EX + i), 8); }
      for (int i = 0; i < NSW; i++) { mbar_init(BAR(B_FW + i), 1); mbar_init(BAR(B_EW + i), 16); }
      asm volatile("fence.mbarrier_init.release.cluster;" ::: "memory");
      fence_async_s();
      for (int i = 0; i < NSW; i++) mbar_expect(BAR(B_FW + i), WSL);
      mbar_expect(BAR(B_FX), 16384);
      tma3(sb, &tmX, 0, par, rt * 128, BAR(B_FX));
    }
  } else if (warp == 13) {
    if (lane == 0) {
      for (int i = 0; i < NS2; i++) { mbar_init(BAR(B_FULL2 + i), 1); mbar_init(BAR(B_EMPTY2 + i), 16); }
      for (int i = 0; i < 5; i++) { mbar_init(BAR(B_XH + i), 5); mbar_init(BAR(B_YDONE + i), 4); }
      mbar_init(BAR(B_SLAB), 1); mbar_init(BAR(B_QS), 1); mbar_init(BAR(B_OST), 8);
      asm volatile("fence.mbarrier_init.release.cluster;" ::: "memory");
      fence_async_s();
    }
  }
  asm volatile("barrier.cluster.arrive.relaxed.aligned;\nbarrier.cluster.wait.aligned;" ::: "memory");

  if (wg < 2) {
    asm volatile("setmaxnreg.inc.sync.aligned.u32 192;");
    constexpr int STW = 1;
    const int g = lane >> 2, t = lane & 3, wq = warp & 3;
    uint32_t qa[10][2];
    const uint32_t tag = *reinterpret_cast<volatile unsigned*>(&g_epoch) + 1;
    {
      float a192[96], a48[24];
      int ws = 0, wph = 0;
#pragma unroll 1
      for (int h = 0; h < 20; h++) {
        const int xs = (h >> 1) & 3;
        if (!(h & 1)) mbar_wait(BAR(B_FX + xs), (h >> 3) & 1);
        mbar_wait(BAR(B_FW + ws), wph);
        if (h == 0) { STAMP(1); CSTAMP(30); }
        if (wg == 0 && !(h & 1)) STAMP(32 + (h >> 1));
        const uint64_t da = mkdesc(sb + xs * 16384 + wg * 8192 + (h & 1) * 64, 16, 1024, 1);
        const uint64_t db = mkdesc(sb + WR_OFF + ws * WSL, 4096, 1024, 1);
        const uint64_t dc = mkdesc(sb + WR_OFF + ws * WSL + 12288, 1024, 256, 3);
        WG_FENCE();
        wg192(a192, da, db, h);
        wg48(a48, da, dc, h);
        wg192(a192, da + 2, db + 128, 1);
        wg48(a48, da + 2, dc + 32, 1);
        WG_COMMIT();
        if (h > 0) {
          WG_WAIT(1);
          if (h <= 20 - NSW && lane < 2) mbar_arrive_cl(BAR(B_EW + (ws == 0 ? NSW - 1 : ws - 1)), lane);
          if (!(h & 1) && h <= 2 * (10 - NSX) && lane == 2) mbar_arrive(BAR(B_EX + ((xs + 3) & 3)));
        }
        if (++ws == NSW) { ws = 0; wph ^= 1; }
      }
      WG_WAIT(0);
      STAMP(2 + wg);
      bar_sync(1, 256);
      const uint32_t kvw = sb + KV_OFF + (8 + 16 * warp + (lane & 7) + 8 * ((lane >> 3) & 1)) * KV_PITCH + (lane >> 4) * 16;
#pragma unroll
      for (int p = 1; p < 3; p++) {
#pragma unroll
        for (int jb = 0; jb < 10; jb += 2) {
          const float* A = jb < 8 ? &a192[(p * 8 + jb) * 4] : &a48[(p * 2) * 4];
          uint32_t r0 = pack2(A[0], A[1]), r1 = pack2(A[2], A[3]), r2 = pack2(A[4], A[5]), r3 = pack2(A[6], A[7]);
          stsm4(kvw + (p - 1) * 160 + jb * 16, r0, r1, r2, r3);
          if (warp == 7 && rt < 7) {
            uint2* hp = g_halo + tid8 * 640 + ((p - 1) * 10 + jb) * 32 + lane;
            asm volatile("st.relaxed.gpu.global.v2.u32 [%0], {%1, %2};" ::"l"(hp), "r"(r1), "r"(tag) : "memory");
            asm volatile("st.relaxed.gpu.global.v2.u32 [%0], {%1, %2};" ::"l"(hp + 32), "r"(r3), "r"(tag) : "memory");
          }
        }
      }
#pragma unroll
      for (int jb = 0; jb < 10; jb++) {
        const float* A = jb < 8 ? &a192[jb * 4] : &a48[(jb - 8) * 4];
        qa[jb][0] = pack2(A[0], A[1]); qa[jb][1] = pack2(A[2], A[3]);
      }
    }
    bar_sync(1, 256);
    STAMP(4 + wg);
    {
      const uint32_t l1 = sb + KV_OFF + (16 * warp + (lane & 7) + 8 * (lane >> 4)) * KV_PITCH + ((lane >> 3) & 1) * 16;
      const uint32_t l2 = sb + KV_OFF + (16 * warp + 16 + (lane & 7)) * KV_PITCH + (lane >> 3) * 16;
      uint32_t f[3][10];
#pragma unroll
      for (int jb = 0; jb < 10; jb += 2) ldsm4(l1 + jb * 16, f[0][jb], f[0][jb + 1], f[1][jb], f[1][jb + 1]);
      ldsm4(l2, f[2][0], f[2][1], f[2][2], f[2][3]);
      ldsm4(l2 + 64, f[2][4], f[2][5], f[2][6], f[2][7]);
      ldsm2(l2 + 128, f[2][8], f[2][9]);
      uint32_t hv[10];
      if (warp == 0) {
#pragma unroll
        for (int j = 0; j < 10; j++) { f[0][j] = 0u; hv[j] = 0u; }
        if (rt > 0) {
          const uint2* hp = g_halo + (tid8 - 8) * 640 + lane;
          for (int it = 0; it < (1 << 17); it++) {
            uint32_t ok = 1;
#pragma unroll
            for (int j = 0; j < 20; j++) {
              uint32_t v, tg;
              asm volatile("ld.relaxed.gpu.global.v2.u32 {%0, %1}, [%2];" : "=r"(v), "=r"(tg) : "l"(hp + j * 32) : "memory");
              if (j < 10) f[0][j] = v; else hv[j - 10] = v;
              ok &= (tg == tag);
            }
            if (__all_sync(~0u, ok)) break;
          }
        }
      }
      const uint32_t mlo = t < 2 ? 0xFFFFFFFFu : 0u;
      const bool sel0 = 2 * t >= g + 1, sel1 = 2 * t + 1 >= g + 1;
      const uint32_t pm = (sel0 ? 0xFFFFu : 0u) | (sel1 ? 0xFFFF0000u : 0u);
      const bool edge = (rt == 0 && warp == 0);
      uint32_t pa[4][2];
      float s[4][3][4];
#pragma unroll
      for (int h = 0; h < 4; h++) {
        const int j16 = (h >> 1) * 5 + (h & 1) * 3;
#pragma unroll
        for (int n = 0; n < 3; n++) {
          s[h][n][0] = s[h][n][1] = s[h][n][2] = s[h][n][3] = 0.f;
          mma16(s[h][n], qa[j16][0], qa[j16][1], qa[j16 + 1][0], qa[j16 + 1][1], f[n][j16], f[n][j16 + 1]);
        }
      }
#pragma unroll
      for (int h = 0; h < 4; h++) {
        const int j8 = (h >> 1) * 5 + 2;
        const uint32_t hm = (h & 1) ? ~mlo : mlo;
#pragma unroll
        for (int n = 0; n < 3; n++) mma8(s[h][n], qa[j8][0] & hm, qa[j8][1] & hm, f[n][j8]);
      }
#pragma unroll
      for (int jb = 0; jb < 10; jb += 2) ldsm4t(l1 + 160 + jb * 16, f[0][jb], f[0][jb + 1], f[1][jb], f[1][jb + 1]);
      ldsm4t(l2 + 160, f[2][0], f[2][1], f[2][2], f[2][3]);
      ldsm4t(l2 + 160 + 64, f[2][4], f[2][5], f[2][6], f[2][7]);
      ldsm2t(l2 + 160 + 128, f[2][8], f[2][9]);
      if (warp == 0) {
#pragma unroll
        for (int j = 0; j < 10; j++) f[0][j] = movtrans(hv[j]);
      }
      float e0[8], e1[8], mx[8];
#pragma unroll
      for (int u = 0; u < 8; u++) {
        const int h = u >> 1, hf = u & 1;
        const float sc = 0.22360679774997896f;
        const uint32_t p = pack2(sel0 ? s[h][hf][2 * hf] : s[h][hf + 1][2 * hf], sel1 ? s[h][hf][2 * hf + 1] : s[h][hf + 1][2 * hf + 1]);
        const uint32_t p2 = pack2(lo2f(p) * sc, hi2f(p) * sc);
        e0[u] = lo2f(p2); e1[u] = hi2f(p2);
        if (hf == 0 && edge) { if (sel0) e0[u] = -1e9f; if (sel1) e1[u] = -1e9f; }
        mx[u] = fmaxf(e0[u], e1[u]);
      }
#pragma unroll
      for (int u = 0; u < 8; u++) mx[u] = fmaxf(mx[u], __shfl_xor_sync(~0u, mx[u], 1));
#pragma unroll
      for (int u = 0; u < 8; u++) mx[u] = fmaxf(mx[u], __shfl_xor_sync(~0u, mx[u], 2));
#pragma unroll
      for (int u = 0; u < 8; u++) {
        e0[u] = ex2f((e0[u] - mx[u]) * 1.4426950408889634f); e1[u] = ex2f((e1[u] - mx[u]) * 1.4426950408889634f);
        mx[u] = e0[u] + e1[u];
      }
#pragma unroll
      for (int u = 0; u < 8; u++) mx[u] += __shfl_xor_sync(~0u, mx[u], 1);
#pragma unroll
      for (int u = 0; u < 8; u++) mx[u] += __shfl_xor_sync(~0u, mx[u], 2);
#pragma unroll
      for (int u = 0; u < 8; u++) { const float r = rcpf(mx[u]); pa[u >> 1][u & 1] = pack2(e0[u] * r, e1[u] * r); }
      uint32_t ob[10][2];
#pragma unroll
      for (int h = 0; h < 4; h++) {
        const int j0 = (h >> 1) * 5 + (h & 1) * 2;
#pragma unroll
        for (int jj = 0; jj < 3; jj++) {
          const int jb = j0 + jj;
          float o[4] = {0.f, 0.f, 0.f, 0.f};
          mma16(o, pa[h][0] & pm, 0u, pa[h][0] & ~pm, pa[h][1] & pm, f[0][jb], f[1][jb]);
          mma8(o, 0u, pa[h][1] & ~pm, f[2][jb]);
          uint32_t u0 = pack2(o[0], o[1]), u1 = pack2(o[2], o[3]);
          if ((h & 1) && jj == 0) { ob[jb][0] = t < 2 ? ob[jb][0] : u0; ob[jb][1] = t < 2 ? ob[jb][1] : u1; }
          else { ob[jb][0] = u0; ob[jb][1] = u1; }
        }
      }
      const uint32_t os = sb + OST_OFF + warp * 2560;
      const uint32_t ow = os + ((lane & 7) + 8 * ((lane >> 3) & 1)) * 160 + (lane >> 4) * 16;
#pragma unroll
      for (int jb = 0; jb < 10; jb += 2) stsm4(ow + jb * 16, ob[jb][0], ob[jb][1], ob[jb + 1][0], ob[jb + 1][1]);
      fence_async_s();
      __syncwarp();
      if (lane == 0) mbar_arrive(BAR(B_OST));
    }
    STAMP(6 + wg);
    const uint32_t xb = sb + XCH_OFF + wg * 16384;
    for (int c = 1 - wg; c < 5; c += 2) {
      const uint32_t cb = sb + CH_OFF + c * CH_SZ;
      mbar_wait(BAR(B_XH + c), 0);
      const uint32_t ab = cb + ((g & 1) ? HA_OFF : HB_OFF) + 4 * ((g >> 1) - 3 + 8 * wq + t);
      const uint64_t db = mkdesc(cb + XR_OFF, 16, 128, 0);
      uint32_t a[64];
      float dA[32], dB[32];
      conv_lda<0, 8>(a, ab);
      WG_FENCE();
      conv_step<3>(dA, a, db);
      conv_step<2>(dB, a, db);
      conv_lda<8, 16>(a, ab);
      if (c < 2) STAMP(26 + wg);
      const bool bw = t < wq;
      const uint32_t xw = xb + wq * 4096 - (bw ? 256 : 0) + (g * 4 + ((t - wq) & 3)) * 8;
      const uint32_t xr = xb + wq * 512 + lane * 8;
      const int sb0 = g + 16 * (127 - t - 8 * wq);
      const uint32_t ys = cb + HB_OFF + 2 * sb0, ks = cb + XR_OFF + 2 * (2047 - sb0);
      const uint32_t dd = lds32(cb);
      float ch[2] = {0.f, 0.f}, cr[2] = {0.f, 0.f};
      WG_WAIT(1);
      conv_epi_a<3>(dA, ch, cr, xw, bw);
      WG_FENCE();
      conv_step<1>(dA, a, db);
      conv_epi_b<3>(xr, ys, ks, dd, 2 + wg);
      WG_WAIT(1);
      conv_epi_a<2>(dB, ch, cr, xw, bw);
      WG_FENCE();
      conv_step<0>(dB, a, db);
      conv_epi_b<2>(xr, ys, ks, dd, 2 + wg);
      WG_WAIT(1);
      conv_epi_a<1>(dA, ch, cr, xw, bw);
      conv_epi_b<1>(xr, ys, ks, dd, 2 + wg);
      WG_WAIT(0);
      if (c < 2) STAMP(8 + wg);
      conv_epi_a<0>(dB, ch, cr, xw, bw);
      conv_epi_b<0>(xr, ys, ks, dd, 2 + wg);
      fence_async_s();
      __syncwarp();
      if (lane == 0) mbar_arrive(BAR(B_YDONE + c));
      if (c < 2) STAMP(10 + wg);
    }
    STAMP(12 + wg);
    {
      float acc[40];
      int slot = 0, ph = 0;
      for (int kb = 0; kb < 10; kb++) {
        mbar_wait(BAR(B_FULL2 + slot), ph);
        if (wg == 0) STAMP(44 + kb);
        const uint32_t st = sb + slot * ST2;
        const uint64_t da = mkdesc(st + wg * 8192, 16, 1024, 1);
        const uint64_t db = mkdesc(st + 16384, 2048, 512, 2);
        WG_FENCE();
#pragma unroll
        for (int k = 0; k < 4; k++) wg80(acc, da + k * 2, db + (k & 1) * 64 + (k >> 1) * 384, kb | k);
        WG_COMMIT();
        if (kb > 0) {
          WG_WAIT(1);
          if (kb <= 10 - NS2 && lane < 2) mbar_arrive_cl(BAR(B_EMPTY2 + (slot == 0 ? NS2 - 1 : slot - 1)), lane);
        }
        if (++slot == NS2) { slot = 0; ph ^= 1; }
      }
      WG_WAIT(0);
      STAMP(14 + wg);
      bar_sync(2 + wg, 128);
      const uint32_t os = xb + wq * 2560;
      const uint32_t ow = os + ((lane & 7) + 8 * ((lane >> 3) & 1)) * 160 + (lane >> 4) * 16;
#pragma unroll
      for (int jb = 0; jb < 10; jb += 2)
        stsm4(ow + jb * 16, pack2(acc[4 * jb], acc[4 * jb + 1]), pack2(acc[4 * jb + 2], acc[4 * jb + 3]),
              pack2(acc[4 * jb + 4], acc[4 * jb + 5]), pack2(acc[4 * jb + 6], acc[4 * jb + 7]));
      fence_async_s();
      __syncwarp();
      if (lane == 0) { tma3_st(&tmOut, 640 + hg * 80, par, rt * 128 + warp * 16, os); bulk_commit(); bulk_wait0(); }
      STAMP(16 + wg); CSTAMP(31);
    }
  } else if (wg == 2) {
    asm volatile("setmaxnreg.dec.sync.aligned.u32 88;");
    const int wi = warp & 3, rh = lane & 1, s0 = 16 * b + 8 * rh, cp0 = 16 * wi + (lane >> 1);
    mbar_wait(BAR(B_SLAB), 0);
    STAMP(19);
    const int j0 = wi * 64 + lane;
    uint4 hw[5][2]; uint32_t hprev[5];
#pragma unroll
    for (int c = 0; c < 5; c++) {
      const uint4* hp = reinterpret_cast<const uint4*>(P.h + (size_t)(128 * c + b) * 2048) + j0;
      hw[c][0] = __ldg(hp); hw[c][1] = __ldg(hp + 32);
      hprev[c] = (lane == 0 && j0 > 0) ? __ldg(reinterpret_cast<const uint32_t*>(hp) - 1) : 0u;
    }
    const uint32_t dv = (wi == 0 && lane < 5) ? (uint32_t)__ldg(reinterpret_cast<const unsigned short*>(P.dvec) + 128 * lane + b) * 0x10001u : 0u;
#pragma unroll 1
    for (int j = 0; j < 5; j++) {
      const int cp = 64 * j + cp0;
      uint32_t kk[11], kv[8];
      uint4 w;
      asm volatile("ld.shared.v4.u32 {%0,%1,%2,%3}, [%4];" : "=r"(w.x), "=r"(w.y), "=r"(w.z), "=r"(w.w) : "r"(sb + SH_OFF + cp * 16) : "memory");
#pragma unroll
      for (int r = 0; r < 11; r++) { kk[r] = lds32(sb + KS_OFF + (8 * rh + r) * 1280 + cp * 4); if (r < 3 && s0 == 0) kk[r] = 0u; }
#pragma unroll
      for (int r = 0; r < 8; r++) kv[r] = lds32(sb + VS_OFF + (8 * rh + r) * 1280 + cp * 4);
      const uint32_t w0 = __byte_perm(w.x, w.z, 0x5410), w1 = __byte_perm(w.x, w.z, 0x7632);
      const uint32_t w2 = __byte_perm(w.y, w.w, 0x5410), w3 = __byte_perm(w.y, w.w, 0x7632);
#pragma unroll
      for (int r = 0; r < 8; r++) {
        uint32_t a = hmul2u(kk[r], w3);
        a = hadd2u(a, hmul2u(kk[r + 1], w2));
        a = hadd2u(a, hmul2u(kk[r + 2], w1));
        a = hadd2u(a, hmul2u(kk[r + 3], w0));
        kv[r] = hmul2u(a, kv[r]);
      }
      uint4* dst = reinterpret_cast<uint4*>(g_xr + (size_t)(2 * cp) * 2048 + (2040 - s0));
      dst[0]   = make_uint4(__byte_perm(kv[7], kv[6], 0x5410), __byte_perm(kv[5], kv[4], 0x5410), __byte_perm(kv[3], kv[2], 0x5410), __byte_perm(kv[1], kv[0], 0x5410));
      dst[256] = make_uint4(__byte_perm(kv[7], kv[6], 0x7632), __byte_perm(kv[5], kv[4], 0x7632), __byte_perm(kv[3], kv[2], 0x7632), __byte_perm(kv[1], kv[0], 0x7632));
    }
    STAMP(42);
    fence_async_g();
    bar_sync(4, 128);
    if (tid == 256) red_release(&g_cnt[CNT_PRE], 1);
    STAMP(18);
    if (wi == 0 && lane < 5) {
      const uint32_t cb = sb + CH_OFF + lane * CH_SZ;
      asm volatile("st.shared.u32 [%0], %1;" ::"r"(cb), "r"(dv) : "memory");
      asm volatile("st.shared.v4.u32 [%0], {%1,%1,%1,%1};" ::"r"(cb + HB_OFF - 16), "r"(0) : "memory");
      asm volatile("st.shared.v4.u32 [%0], {%1,%1,%1,%1};" ::"r"(cb + HA_OFF - 16), "r"(0) : "memory");
      asm volatile("st.shared.v4.u32 [%0], {%1,%1,%1,%1};" ::"r"(cb + XR_OFF + 4096), "r"(0) : "memory");
      fence_async_s();
    }
#pragma unroll
    for (int c = 0; c < 5; c++) {
      const uint32_t cb = sb + CH_OFF + c * CH_SZ + j0 * 16;
      uint32_t prev = hprev[c];
#pragma unroll
      for (int i = 0; i < 2; i++) {
        const uint4 w = hw[c][i];
        uint32_t up = __shfl_up_sync(~0u, w.w, 1);
        if (lane == 0) up = prev;
        prev = __shfl_sync(~0u, w.w, 31);
        asm volatile("st.shared.v4.u32 [%0], {%1,%2,%3,%4};" ::"r"(cb + HA_OFF + 512 * i), "r"(w.x), "r"(w.y), "r"(w.z), "r"(w.w) : "memory");
        asm volatile("st.shared.v4.u32 [%0], {%1,%2,%3,%4};" ::"r"(cb + HB_OFF + 512 * i), "r"(__byte_perm(up, w.x, 0x5432)),
                     "r"(__byte_perm(w.x, w.y, 0x5432)), "r"(__byte_perm(w.y, w.z, 0x5432)), "r"(__byte_perm(w.z, w.w, 0x5432)) : "memory");
      }
    }
    __syncwarp();
    if (lane < 5) mbar_arrive(BAR(B_XH + lane));
    STAMP(25);
    mbar_wait(BAR(B_QS), 0);
    uint32_t* op = reinterpret_cast<uint32_t*>(P.out) + (size_t)s0 * 640 + cp0;
#pragma unroll 1
    for (int jj = 0; jj < 5; jj++) {
      const int j = jj == 0 ? 0 : jj == 1 ? 1 : jj == 2 ? 2 : jj == 3 ? 3 : 4;
      if (lane == 0) wait_ge(&g_cnt[CNT_Y(j)], 128);
      __syncwarp();
      if (jj == 4) STAMP(20);
      const uint4* src = reinterpret_cast<const uint4*>(g_y + (size_t)(2 * (64 * j + cp0)) * 2048 + s0);
      const uint4 ya = __ldcg(src), yb = __ldcg(src + 256);
      const uint32_t qs = sb + QS_OFF + 8 * rh * 1280 + (64 * j + cp0) * 4;
      const uint32_t A[4] = {ya.x, ya.y, ya.z, ya.w}, B[4] = {yb.x, yb.y, yb.z, yb.w};
#pragma unroll
      for (int r = 0; r < 4; r++) {
        op[(2 * r) * 640 + 64 * j] = hmul2u(lds32(qs + (2 * r) * 1280), __byte_perm(A[r], B[r], 0x5410));
        op[(2 * r + 1) * 640 + 64 * j] = hmul2u(lds32(qs + (2 * r + 1) * 1280), __byte_perm(A[r], B[r], 0x7632));
      }
    }
    if (lane == 0) { EXIT_COUNT(); }
    STAMP(21);
  } else {
    asm volatile("setmaxnreg.dec.sync.aligned.u32 40;");
    if (warp == 12) {
      if (lane == 0) {
#pragma unroll 1
        for (int h = 0; h < 20; h++) {
          const int ws = h % NSW;
          if (h >= NSW) {
            mbar_wait(BAR(B_EW + ws), ((h / NSW) - 1) & 1);
            mbar_expect(BAR(B_FW + ws), WSL);
          }
          if ((h & 1) == rank) {
            tma3mc(sb + WR_OFF + ws * WSL, &tmW64, hg * 80, h * 32, 0, BAR(B_FW + ws));
            tma3mc(sb + WR_OFF + ws * WSL + 12288, &tmW16, hg * 80 + 64, h * 32, 0, BAR(B_FW + ws));
          }
          const int kb = (h + 1) >> 1;
          if ((h & 1) && kb < 10) {
            if (kb >= NSX) mbar_wait(BAR(B_EX + (kb & 3)), ((kb >> 2) - 1) & 1);
            mbar_expect(BAR(B_FX + (kb & 3)), 16384);
            tma3(sb + (kb & 3) * 16384, &tmX, kb * 64, par, rt * 128, BAR(B_FX + (kb & 3)));
          }
        }
        wait_ge(&g_cnt[CNT_O(tt)], 8);
        wait_ge(&g_cnt[CNT_O(tt ^ 1)], 8);
        fence_async_g();
        STAMP(22);
        for (int kb = 0; kb < 10; kb++) {
          const int slot = kb % NS2;
          if (kb >= NS2) mbar_wait(BAR(B_EMPTY2 + slot), ((kb / NS2) - 1) & 1);
          uint32_t st = sb + slot * ST2, fb = BAR(B_FULL2 + slot);
          mbar_expect(fb, ST2);
          for (int a = 0; a < 3; a++) tma2mc(st + 16384 + rank * 6144 + a * 2048, &tmWo, hg * 80 + a * 32, kb * 64 + rank * 32, fb);
          tma2(st, &tmOld, kb * 64, tt * 128, fb);
        }
        EXIT_COUNT();
      }
    } else if (warp == 13) {
      constexpr int STW = 1;
      if (lane < 16) l2_prefetch(reinterpret_cast<const char*>(P.x) + (size_t)(16 * b + lane) * 1280 + 384, 896);
      else if (lane == 16) l2_prefetch(reinterpret_cast<const char*>(P.wqkv) + 160 * 3840 + b * 14400, 14400);
      if (lane == 0) {
        mbar_wait(BAR(B_FW), 0);
        const int skip = b == 0 ? 3 : 0;
        mbar_expect(BAR(B_SLAB), (35 - skip) * 1280 + 5120);
        bulk_ld(sb + KS_OFF + skip * 1280, P.k + (size_t)(16 * b - 3 + skip) * 640, (19 - skip) * 1280, BAR(B_SLAB));
        bulk_ld(sb + VS_OFF, P.v + (size_t)(16 * b) * 640, 16 * 1280, BAR(B_SLAB));
        bulk_ld(sb + SH_OFF, P.shift, 5120, BAR(B_SLAB));
        wait_ge(&g_cnt[CNT_PRE], 128);
        STAMP(23);
        fence_async_g();
        for (int c = 0; c < 5; c++) {
          mbar_expect(BAR(B_XH + c), 4096);
          bulk_ld(sb + CH_OFF + c * CH_SZ + XR_OFF, g_xr + (size_t)(128 * c + b) * 2048, 4096, BAR(B_XH + c));
        }
        l2_prefetch(reinterpret_cast<const char*>(P.wo) + b * 6400, 6400);
        mbar_expect(BAR(B_QS), 20480);
        bulk_ld(sb + QS_OFF, P.q + (size_t)(16 * b) * 640, 20480, BAR(B_QS));
        EXIT_COUNT();
      }
    } else if (lane == 0) {
      constexpr int STW = 2;
      if (warp == 14) {
        mbar_wait(BAR(B_OST), 0);
        STAMP(28);
        tma2_st(&tmOst, hg * 80, tt * 128, sb + OST_OFF);
        bulk_commit(); bulk_wait0(); fence_async_g();
        red_relaxed(&g_cnt[CNT_O(tt)], 1);
        STAMP(29);
      } else {
#pragma unroll 1
        for (int c = 0; c < 5; c++) {
          mbar_wait(BAR(B_YDONE + c), 0);
          bulk_st(g_y + (size_t)(128 * c + b) * 2048, sb + CH_OFF + c * CH_SZ + HB_OFF, 4096);
          bulk_commit(); bulk_wait0(); fence_async_g();
          red_relaxed(&g_cnt[CNT_Y(c)], 1);
        }
      }
    }
  }
}

typedef CUresult (*EncFn)(CUtensorMap*, CUtensorMapDataType, cuuint32_t, void*, const cuuint64_t*, const cuuint64_t*, const cuuint32_t*,
                          const cuuint32_t*, CUtensorMapInterleave, CUtensorMapSwizzle, CUtensorMapL2promotion, CUtensorMapFloatOOBfill);

static void enc(EncFn fn, CUtensorMap* m, const void* base, int rank, const cuuint64_t* dims, const cuuint64_t* strides, const cuuint32_t* box,
                CUtensorMapSwizzle sw) {
  cuuint32_t es[3] = {1, 1, 1};
  fn(m, CU_TENSOR_MAP_DATA_TYPE_BFLOAT16, rank, const_cast<void*>(base), dims, strides, box, es, CU_TENSOR_MAP_INTERLEAVE_NONE, sw,
     CU_TENSOR_MAP_L2_PROMOTION_L2_128B, CU_TENSOR_MAP_FLOAT_OOB_FILL_NONE);
}

extern "C" void kernel_launch(void* const* d_in, const int* in_sizes, int n_in, void* d_out, int out_size) {
  static EncFn fn = nullptr;
  static void* o_ptr = nullptr;
  if (!fn) {
    cudaDriverEntryPointQueryResult qr;
    cudaGetDriverEntryPoint("cuTensorMapEncodeTiled", (void**)&fn, cudaEnableDefault, &qr);
    cudaFuncSetAttribute(fused_kernel, cudaFuncAttributeMaxDynamicSharedMemorySize, SMEM_BYTES);
    cudaGetSymbolAddress(&o_ptr, g_o);
  }
  Params P;
  P.q = (const bf16*)d_in[0]; P.k = (const bf16*)d_in[1]; P.v = (const bf16*)d_in[2]; P.shift = (const bf16*)d_in[3];
  P.h = (const bf16*)d_in[4]; P.dvec = (const bf16*)d_in[5]; P.x = (const bf16*)d_in[6]; P.wqkv = (const bf16*)d_in[7];
  P.wo = (const bf16*)d_in[8]; P.out = (bf16*)d_out;
  CUtensorMap tmX, tmW64, tmW16, tmWo, tmOld, tmOst, tmOut;
  { cuuint64_t d[3] = {640, 2, 1024}, s[2] = {1280, 2560}; cuuint32_t bx[3] = {64, 1, 128}; enc(fn, &tmX, P.x, 3, d, s, bx, CU_TENSOR_MAP_SWIZZLE_128B); }
  { cuuint64_t d[3] = {640, 640, 3}, s[2] = {3840, 1280}; cuuint32_t bx[3] = {64, 32, 3}; enc(fn, &tmW64, P.wqkv, 3, d, s, bx, CU_TENSOR_MAP_SWIZZLE_128B); }
  { cuuint64_t d[3] = {640, 640, 3}, s[2] = {3840, 1280}; cuuint32_t bx[3] = {16, 32, 3}; enc(fn, &tmW16, P.wqkv, 3, d, s, bx, CU_TENSOR_MAP_SWIZZLE_32B); }
  { cuuint64_t d[2] = {640, 640}, s[1] = {1280}; cuuint32_t bx[2] = {32, 32}; enc(fn, &tmWo, P.wo, 2, d, s, bx, CU_TENSOR_MAP_SWIZZLE_64B); }
  { cuuint64_t d[2] = {640, 2048}, s[1] = {1280}; cuuint32_t bx[2] = {64, 128}; enc(fn, &tmOld, o_ptr, 2, d, s, bx, CU_TENSOR_MAP_SWIZZLE_128B); }
  { cuuint64_t d[2] = {640, 2048}, s[1] = {1280}; cuuint32_t bx[2] = {80, 128}; enc(fn, &tmOst, o_ptr, 2, d, s, bx, CU_TENSOR_MAP_SWIZZLE_NONE); }
  { cuuint64_t d[3] = {1280, 2, 1024}, s[2] = {2560, 5120}; cuuint32_t bx[3] = {80, 1, 16}; enc(fn, &tmOut, P.out, 3, d, s, bx, CU_TENSOR_MAP_SWIZZLE_NONE); }
  fused_kernel<<<128, 512, SMEM_BYTES>>>(tmX, tmW64, tmW16, tmWo, tmOld, tmOst, tmOut, P);
}
```

```cpp
#include <cuda_runtime.h>
#include <cuda_bf16.h>
#include <cuda.h>
#include <stdint.h>

typedef __nv_bfloat16 bf16;
typedef __nv_bfloat162 bf162;

__device__ __align__(1024) bf16 g_o[2048 * 640];
__device__ __align__(1024) bf16 g_xr[640 * 2048];
__device__ __align__(1024) bf16 g_y[640 * 2048];
__device__ __align__(1024) uint2 g_halo[128 * 640];
__device__ unsigned g_epoch;
constexpr int NCNT = 32 * 28;
__device__ __align__(128) unsigned g_cnt[NCNT];
#define CNT_PRE(j) (736 + 32 * (j))
#define CNT_EXIT 32
#define CNT_O(tt) (64 + 32 * (tt))
#define CNT_Y(c) (576 + 32 * (c))
#define KS(cond, i)
#define CSTAMP(i)
#define STAMP(i)

constexpr int NSX = 4, NSW = 5;
constexpr int WR_OFF = NSX * 16384;
constexpr int WSL = 15360;
#define PF0_NS 100
#define PF1_SLOT 0
#define KV_SLOT 0
#define PFA_SLOT 1
#define B2_KW 3
#define KV_FL 1
constexpr int KV_OFF = 0;
constexpr int KV_PITCH = 336;
constexpr int OST_OFF = 49152;
constexpr int ST2 = 28672;
constexpr int NS2 = 5;
constexpr int XCH_OFF = 4 * ST2;
constexpr int CH_OFF = XCH_OFF + 32768;
constexpr int CH_SZ = 12416;
constexpr int XR_OFF = 0, DV_OFF = 4112, HB_OFF = 4160, HA_OFF = 8320;
constexpr int KS_OFF = CH_OFF, KS_H = 11 * 1280 + 64, VS_OFF = KS_OFF + 2 * KS_H, VS_H = 8 * 1280 + 64, SH_OFF = VS_OFF + 2 * VS_H;
constexpr int XC2_OFF = CH_OFF + 5 * CH_SZ;
constexpr int BAR_OFF = XC2_OFF + 20480;
constexpr int SMEM_BYTES = BAR_OFF + 512 + 1024;
enum { B_FX = 0, B_EX = 4, B_FW = 8, B_EW = 13, B_FULL2 = 18, B_XFREE = 23, B_EMPTY2 = 44, B_XH = 26, B_YDONE = 31, B_OST = 38, B_PST = 39, B_COUNT = 49 };

__device__ __forceinline__ uint32_t s2u(const void* p) { return (uint32_t)__cvta_generic_to_shared(p); }
__device__ __forceinline__ void mbar_init(uint32_t a, int c) { asm volatile("mbarrier.init.shared.b64 [%0], %1;" ::"r"(a), "r"(c) : "memory"); }
__device__ __forceinline__ void mbar_expect(uint32_t a, uint32_t b) { asm volatile("mbarrier.arrive.expect_tx.shared.b64 _, [%0], %1;" ::"r"(a), "r"(b) : "memory"); }
__device__ __forceinline__ void mbar_arrive(uint32_t a) { asm volatile("mbarrier.arrive.shared.b64 _, [%0];" ::"r"(a) : "memory"); }
__device__ __forceinline__ void mbar_wait(uint32_t a, uint32_t ph) {
#pragma unroll 1
  for (int i = 0; i < (1 << 15); i++) {
    uint32_t ok;
    asm volatile("{\n.reg .pred p;\nmbarrier.try_wait.parity.shared.b64 p, [%1], %2;\nselp.u32 %0, 1, 0, p;\n}" : "=r"(ok) : "r"(a), "r"(ph) : "memory");
    if (ok) return;
  }
}
__device__ __forceinline__ void wait_ge(const unsigned* p, unsigned target) {
#pragma unroll 1
  for (int i = 0; i < (1 << 16); i++) {
    unsigned v;
    asm volatile("ld.acquire.gpu.global.u32 %0, [%1];" : "=r"(v) : "l"(p) : "memory");
    if (v >= target) return;
    __nanosleep(40);
  }
}
__device__ __forceinline__ void red_release(unsigned* p, unsigned v) { asm volatile("red.release.gpu.global.add.u32 [%0], %1;" ::"l"(p), "r"(v) : "memory"); }
__device__ __forceinline__ void red_relaxed(unsigned* p, unsigned v) { asm volatile("red.relaxed.gpu.global.add.u32 [%0], %1;" ::"l"(p), "r"(v) : "memory"); }
__device__ __forceinline__ uint32_t movtrans(uint32_t a) { uint32_t r; asm volatile("movmatrix.sync.aligned.m8n8.trans.b16 %0, %1;" : "=r"(r) : "r"(a)); return r; }
__device__ __forceinline__ void fence_async_s() { asm volatile("fence.proxy.async.shared::cta;" ::: "memory"); }
__device__ __forceinline__ void fence_async_g() { asm volatile("fence.proxy.async.global;" ::: "memory"); }
__device__ __forceinline__ void bar_sync(int id, int n) { asm volatile("bar.sync %0, %1;" ::"r"(id), "r"(n) : "memory"); }
__device__ __forceinline__ void tma2(uint32_t dst, const CUtensorMap* m, int c0, int c1, uint32_t bar) {
  asm volatile("cp.async.bulk.tensor.2d.shared::cluster.global.mbarrier::complete_tx::bytes [%0], [%1, {%3, %4}], [%2];" ::"r"(dst), "l"(m), "r"(bar), "r"(c0), "r"(c1) : "memory");
}
__device__ __forceinline__ void tma3(uint32_t dst, const CUtensorMap* m, int c0, int c1, int c2, uint32_t bar) {
  asm volatile("cp.async.bulk.tensor.3d.shared::cluster.global.mbarrier::complete_tx::bytes [%0], [%1, {%3, %4, %5}], [%2];" ::"r"(dst), "l"(m), "r"(bar), "r"(c0), "r"(c1), "r"(c2) : "memory");
}
__device__ __forceinline__ void tma2mc(uint32_t dst, const CUtensorMap* m, int c0, int c1, uint32_t bar) {
  asm volatile("cp.async.bulk.tensor.2d.shared::cluster.global.mbarrier::complete_tx::bytes.multicast::cluster [%0], [%1, {%3, %4}], [%2], %5;" ::"r"(dst), "l"(m), "r"(bar), "r"(c0), "r"(c1), "h"((uint16_t)3) : "memory");
}
__device__ __forceinline__ void tma3mc(uint32_t dst, const CUtensorMap* m, int c0, int c1, int c2, uint32_t bar) {
  asm volatile("cp.async.bulk.tensor.3d.shared::cluster.global.mbarrier::complete_tx::bytes.multicast::cluster [%0], [%1, {%3, %4, %5}], [%2], %6;" ::"r"(dst), "l"(m), "r"(bar), "r"(c0), "r"(c1), "r"(c2), "h"((uint16_t)3) : "memory");
}
__device__ __forceinline__ void mbar_arrive_cl(uint32_t a, uint32_t rank) {
  asm volatile("{\n.reg .b32 r;\nmapa.shared::cluster.u32 r, %0, %1;\nmbarrier.arrive.shared::cluster.b64 _, [r];\n}" ::"r"(a), "r"(rank) : "memory");
}
__device__ __forceinline__ void tma2_st(const CUtensorMap* m, int c0, int c1, uint32_t src) {
  asm volatile("cp.async.bulk.tensor.2d.global.shared::cta.bulk_group [%0, {%2, %3}], [%1];" ::"l"(m), "r"(src), "r"(c0), "r"(c1) : "memory");
}
__device__ __forceinline__ void tma3_st(const CUtensorMap* m, int c0, int c1, int c2, uint32_t src) {
  asm volatile("cp.async.bulk.tensor.3d.global.shared::cta.bulk_group [%0, {%2, %3, %4}], [%1];" ::"l"(m), "r"(src), "r"(c0), "r"(c1), "r"(c2) : "memory");
}
__device__ __forceinline__ void bulk_ld(uint32_t dst, const void* src, uint32_t n, uint32_t bar) {
  asm volatile("cp.async.bulk.shared::cluster.global.mbarrier::complete_tx::bytes [%0], [%1], %2, [%3];" ::"r"(dst), "l"(src), "r"(n), "r"(bar) : "memory");
}
__device__ __forceinline__ void bulk_st(void* dst, uint32_t src, uint32_t n) {
  asm volatile("cp.async.bulk.global.shared::cta.bulk_group [%0], [%1], %2;" ::"l"(dst), "r"(src), "r"(n) : "memory");
}
__device__ __forceinline__ void pf_lines(const void* src, int n, int lane) {
  for (int o = lane * 128; o < n; o += 4096) asm volatile("prefetch.global.L2 [%0];" ::"l"(reinterpret_cast<const char*>(src) + o) : "memory");
}
__device__ __forceinline__ void cp16(uint32_t dst, const void* src) { asm volatile("cp.async.cg.shared.global [%0], [%1], 16;" ::"r"(dst), "l"(src) : "memory"); }
__device__ __forceinline__ void bulk_commit() { asm volatile("cp.async.bulk.commit_group;" ::: "memory"); }
__device__ __forceinline__ void bulk_wait0() { asm volatile("cp.async.bulk.wait_group 0;" ::: "memory"); }
#define WG_FENCE() asm volatile("wgmma.fence.sync.aligned;" ::: "memory")
#define WG_COMMIT() asm volatile("wgmma.commit_group.sync.aligned;" ::: "memory")
#define WG_WAIT(n) asm volatile("wgmma.wait_group.sync.aligned " #n ";" ::: "memory")
__device__ __forceinline__ uint64_t mkdesc(uint32_t addr, uint32_t lbo, uint32_t sbo, uint32_t lt) {
  return (uint64_t)((addr & 0x3FFFF) >> 4) | ((uint64_t)(lbo >> 4) << 16) | ((uint64_t)(sbo >> 4) << 32) | ((uint64_t)lt << 62);
}
__device__ __forceinline__ uint32_t pack2(float lo, float hi) { uint32_t r; asm("cvt.rn.bf16x2.f32 %0, %1, %2;" : "=r"(r) : "f"(hi), "f"(lo)); return r; }
__device__ __forceinline__ float lo2f(uint32_t p) { return __uint_as_float(p << 16); }
__device__ __forceinline__ float hi2f(uint32_t p) { return __uint_as_float(p & 0xFFFF0000u); }
__device__ __forceinline__ float ex2f(float x) { float r; asm("ex2.approx.ftz.f32 %0, %1;" : "=f"(r) : "f"(x)); return r; }
__device__ __forceinline__ float rcpf(float x) { float r; asm("rcp.approx.ftz.f32 %0, %1;" : "=f"(r) : "f"(x)); return r; }
__device__ __forceinline__ void stsm4(uint32_t a, uint32_t r0, uint32_t r1, uint32_t r2, uint32_t r3) {
  asm volatile("stmatrix.sync.aligned.m8n8.x4.shared.b16 [%0], {%1, %2, %3, %4};" ::"r"(a), "r"(r0), "r"(r1), "r"(r2), "r"(r3) : "memory");
}
__device__ __forceinline__ void ldsm4(uint32_t a, uint32_t& r0, uint32_t& r1, uint32_t& r2, uint32_t& r3) {
  asm volatile("ldmatrix.sync.aligned.m8n8.x4.shared.b16 {%0, %1, %2, %3}, [%4];" : "=r"(r0), "=r"(r1), "=r"(r2), "=r"(r3) : "r"(a) : "memory");
}
__device__ __forceinline__ void ldsm2(uint32_t a, uint32_t& r0, uint32_t& r1) {
  asm volatile("ldmatrix.sync.aligned.m8n8.x2.shared.b16 {%0, %1}, [%2];" : "=r"(r0), "=r"(r1) : "r"(a) : "memory");
}
__device__ __forceinline__ void ldsm4t(uint32_t a, uint32_t& r0, uint32_t& r1, uint32_t& r2, uint32_t& r3) {
  asm volatile("ldmatrix.sync.aligned.m8n8.x4.trans.shared.b16 {%0, %1, %2, %3}, [%4];" : "=r"(r0), "=r"(r1), "=r"(r2), "=r"(r3) : "r"(a) : "memory");
}
__device__ __forceinline__ void ldsm2t(uint32_t a, uint32_t& r0, uint32_t& r1) {
  asm volatile("ldmatrix.sync.aligned.m8n8.x2.trans.shared.b16 {%0, %1}, [%2];" : "=r"(r0), "=r"(r1) : "r"(a) : "memory");
}
__device__ __forceinline__ void mma16(float (&c)[4], uint32_t a0, uint32_t a1, uint32_t a2, uint32_t a3, uint32_t b0, uint32_t b1) {
  asm("mma.sync.aligned.m16n8k16.row.col.f32.bf16.bf16.f32 {%0,%1,%2,%3}, {%4,%5,%6,%7}, {%8,%9}, {%0,%1,%2,%3};"
               : "+f"(c[0]), "+f"(c[1]), "+f"(c[2]), "+f"(c[3]) : "r"(a0), "r"(a1), "r"(a2), "r"(a3), "r"(b0), "r"(b1));
}
__device__ __forceinline__ void mma8(float (&c)[4], uint32_t a0, uint32_t a1, uint32_t b0) {
  asm("mma.sync.aligned.m16n8k8.row.col.f32.bf16.bf16.f32 {%0,%1,%2,%3}, {%4,%5}, {%6}, {%0,%1,%2,%3};"
               : "+f"(c[0]), "+f"(c[1]), "+f"(c[2]), "+f"(c[3]) : "r"(a0), "r"(a1), "r"(b0));
}
__device__ __forceinline__ uint32_t lds32(uint32_t a) { uint32_t v; asm volatile("ld.shared.u32 %0, [%1];" : "=r"(v) : "r"(a) : "memory"); return v; }
__device__ __forceinline__ uint32_t lds16(uint32_t a) { uint16_t v; asm volatile("ld.shared.u16 %0, [%1];" : "=h"(v) : "r"(a) : "memory"); return v; }
__device__ __forceinline__ void sts16(uint32_t a, uint16_t v) { asm volatile("st.shared.u16 [%0], %1;" ::"r"(a), "h"(v) : "memory"); }
__device__ __forceinline__ void sts64f(uint32_t a, float x, float y) { asm volatile("st.shared.v2.f32 [%0], {%1, %2};" ::"r"(a), "f"(x), "f"(y) : "memory"); }
__device__ __forceinline__ float2 lds64f(uint32_t a) { float2 v; asm volatile("ld.shared.v2.f32 {%0, %1}, [%2];" : "=f"(v.x), "=f"(v.y) : "r"(a) : "memory"); return v; }
__device__ __forceinline__ uint32_t hmul2u(uint32_t a, uint32_t b) { uint32_t r; asm("mul.rn.bf16x2 %0, %1, %2;" : "=r"(r) : "r"(a), "r"(b)); return r; }
__device__ __forceinline__ uint32_t hadd2u(uint32_t a, uint32_t b) { uint32_t r; asm("add.rn.bf16x2 %0, %1, %2;" : "=r"(r) : "r"(a), "r"(b)); return r; }

__device__ __forceinline__ void wg192(float (&d)[96], uint64_t da, uint64_t db, int sc) {
  asm volatile("{\n.reg .pred p;\nsetp.ne.b32 p, %98, 0;\n"
    "wgmma.mma_async.sync.aligned.m64n192k16.f32.bf16.bf16 {%0, %1, %2, %3, %4, %5, %6, %7, %8, %9, %10, %11, %12, %13, %14, %15, %16, %17, %18, %19, %20, %21, %22, %23, %24, %25, %26, %27, %28, %29, %30, %31, %32, %33, %34, %35, %36, %37, %38, %39, %40, %41, %42, %43, %44, %45, %46, %47, %48, %49, %50, %51, %52, %53, %54, %55, %56, %57, %58, %59, %60, %61, %62, %63, %64, %65, %66, %67, %68, %69, %70, %71, %72, %73, %74, %75, %76, %77, %78, %79, %80, %81, %82, %83, %84, %85, %86, %87, %88, %89, %90, %91, %92, %93, %94, %95}, %96, %97, p, 1, 1, 0, 1;\n}"
    : "+f"(d[0]), "+f"(d[1]), "+f"(d[2]), "+f"(d[3]), "+f"(d[4]), "+f"(d[5]), "+f"(d[6]), "+f"(d[7]), "+f"(d[8]), "+f"(d[9]), "+f"(d[10]), "+f"(d[11]), "+f"(d[12]), "+f"(d[13]), "+f"(d[14]), "+f"(d[15]), "+f"(d[16]), "+f"(d[17]), "+f"(d[18]), "+f"(d[19]), "+f"(d[20]), "+f"(d[21]), "+f"(d[22]), "+f"(d[23]), "+f"(d[24]), "+f"(d[25]), "+f"(d[26]), "+f"(d[27]), "+f"(d[28]), "+f"(d[29]), "+f"(d[30]), "+f"(d[31]), "+f"(d[32]), "+f"(d[33]), "+f"(d[34]), "+f"(d[35]), "+f"(d[36]), "+f"(d[37]), "+f"(d[38]), "+f"(d[39]), "+f"(d[40]), "+f"(d[41]), "+f"(d[42]), "+f"(d[43]), "+f"(d[44]), "+f"(d[45]), "+f"(d[46]), "+f"(d[47]), "+f"(d[48]), "+f"(d[49]), "+f"(d[50]), "+f"(d[51]), "+f"(d[52]), "+f"(d[53]), "+f"(d[54]), "+f"(d[55]), "+f"(d[56]), "+f"(d[57]), "+f"(d[58]), "+f"(d[59]), "+f"(d[60]), "+f"(d[61]), "+f"(d[62]), "+f"(d[63]), "+f"(d[64]), "+f"(d[65]), "+f"(d[66]), "+f"(d[67]), "+f"(d[68]), "+f"(d[69]), "+f"(d[70]), "+f"(d[71]), "+f"(d[72]), "+f"(d[73]), "+f"(d[74]), "+f"(d[75]), "+f"(d[76]), "+f"(d[77]), "+f"(d[78]), "+f"(d[79]), "+f"(d[80]), "+f"(d[81]), "+f"(d[82]), "+f"(d[83]), "+f"(d[84]), "+f"(d[85]), "+f"(d[86]), "+f"(d[87]), "+f"(d[88]), "+f"(d[89]), "+f"(d[90]), "+f"(d[91]), "+f"(d[92]), "+f"(d[93]), "+f"(d[94]), "+f"(d[95])
    : "l"(da), "l"(db), "r"(sc));
}
__device__ __forceinline__ void wg48(float (&d)[24], uint64_t da, uint64_t db, int sc) {
  asm volatile("{\n.reg .pred p;\nsetp.ne.b32 p, %26, 0;\n"
    "wgmma.mma_async.sync.aligned.m64n48k16.f32.bf16.bf16 {%0, %1, %2, %3, %4, %5, %6, %7, %8, %9, %10, %11, %12, %13, %14, %15, %16, %17, %18, %19, %20, %21, %22, %23}, %24, %25, p, 1, 1, 0, 1;\n}"
    : "+f"(d[0]), "+f"(d[1]), "+f"(d[2]), "+f"(d[3]), "+f"(d[4]), "+f"(d[5]), "+f"(d[6]), "+f"(d[7]), "+f"(d[8]), "+f"(d[9]), "+f"(d[10]), "+f"(d[11]), "+f"(d[12]), "+f"(d[13]), "+f"(d[14]), "+f"(d[15]), "+f"(d[16]), "+f"(d[17]), "+f"(d[18]), "+f"(d[19]), "+f"(d[20]), "+f"(d[21]), "+f"(d[22]), "+f"(d[23])
    : "l"(da), "l"(db), "r"(sc));
}
__device__ __forceinline__ void wg80(float (&d)[40], uint64_t da, uint64_t db, int sc) {
  asm volatile("{\n.reg .pred p;\nsetp.ne.b32 p, %42, 0;\n"
    "wgmma.mma_async.sync.aligned.m64n80k16.f32.bf16.bf16 {%0, %1, %2, %3, %4, %5, %6, %7, %8, %9, %10, %11, %12, %13, %14, %15, %16, %17, %18, %19, %20, %21, %22, %23, %24, %25, %26, %27, %28, %29, %30, %31, %32, %33, %34, %35, %36, %37, %38, %39}, %40, %41, p, 1, 1, 0, 1;\n}"
    : "+f"(d[0]), "+f"(d[1]), "+f"(d[2]), "+f"(d[3]), "+f"(d[4]), "+f"(d[5]), "+f"(d[6]), "+f"(d[7]), "+f"(d[8]), "+f"(d[9]), "+f"(d[10]), "+f"(d[11]), "+f"(d[12]), "+f"(d[13]), "+f"(d[14]), "+f"(d[15]), "+f"(d[16]), "+f"(d[17]), "+f"(d[18]), "+f"(d[19]), "+f"(d[20]), "+f"(d[21]), "+f"(d[22]), "+f"(d[23]), "+f"(d[24]), "+f"(d[25]), "+f"(d[26]), "+f"(d[27]), "+f"(d[28]), "+f"(d[29]), "+f"(d[30]), "+f"(d[31]), "+f"(d[32]), "+f"(d[33]), "+f"(d[34]), "+f"(d[35]), "+f"(d[36]), "+f"(d[37]), "+f"(d[38]), "+f"(d[39])
    : "l"(da), "l"(db), "r"(sc));
}
template <int N, int SC> __device__ __forceinline__ void cvm(float* d, const uint32_t* a, uint64_t db);
template <> __device__ __forceinline__ void cvm<64, 0>(float* d, const uint32_t* a, uint64_t db) {
  asm volatile("wgmma.mma_async.sync.aligned.m64n64k16.f32.bf16.bf16 {%0, %1, %2, %3, %4, %5, %6, %7, %8, %9, %10, %11, %12, %13, %14, %15, %16, %17, %18, %19, %20, %21, %22, %23, %24, %25, %26, %27, %28, %29, %30, %31}, {%32,%33,%34,%35}, %36, 0, 1, 1, 0;"
    : "=f"(d[0]), "=f"(d[1]), "=f"(d[2]), "=f"(d[3]), "=f"(d[4]), "=f"(d[5]), "=f"(d[6]), "=f"(d[7]), "=f"(d[8]), "=f"(d[9]), "=f"(d[10]), "=f"(d[11]), "=f"(d[12]), "=f"(d[13]), "=f"(d[14]), "=f"(d[15]), "=f"(d[16]), "=f"(d[17]), "=f"(d[18]), "=f"(d[19]), "=f"(d[20]), "=f"(d[21]), "=f"(d[22]), "=f"(d[23]), "=f"(d[24]), "=f"(d[25]), "=f"(d[26]), "=f"(d[27]), "=f"(d[28]), "=f"(d[29]), "=f"(d[30]), "=f"(d[31])
    : "r"(a[0]), "r"(a[1]), "r"(a[2]), "r"(a[3]), "l"(db));
}
template <> __device__ __forceinline__ void cvm<16, 1>(float* d, const uint32_t* a, uint64_t db) {
  asm volatile("wgmma.mma_async.sync.aligned.m64n16k16.f32.bf16.bf16 {%0, %1, %2, %3, %4, %5, %6, %7}, {%8,%9,%10,%11}, %12, 1, 1, 1, 0;"
    : "+f"(d[0]), "+f"(d[1]), "+f"(d[2]), "+f"(d[3]), "+f"(d[4]), "+f"(d[5]), "+f"(d[6]), "+f"(d[7])
    : "r"(a[0]), "r"(a[1]), "r"(a[2]), "r"(a[3]), "l"(db));
}
template <> __device__ __forceinline__ void cvm<32, 1>(float* d, const uint32_t* a, uint64_t db) {
  asm volatile("wgmma.mma_async.sync.aligned.m64n32k16.f32.bf16.bf16 {%0, %1, %2, %3, %4, %5, %6, %7, %8, %9, %10, %11, %12, %13, %14, %15}, {%16,%17,%18,%19}, %20, 1, 1, 1, 0;"
    : "+f"(d[0]), "+f"(d[1]), "+f"(d[2]), "+f"(d[3]), "+f"(d[4]), "+f"(d[5]), "+f"(d[6]), "+f"(d[7]), "+f"(d[8]), "+f"(d[9]), "+f"(d[10]), "+f"(d[11]), "+f"(d[12]), "+f"(d[13]), "+f"(d[14]), "+f"(d[15])
    : "r"(a[0]), "r"(a[1]), "r"(a[2]), "r"(a[3]), "l"(db));
}
template <> __device__ __forceinline__ void cvm<48, 1>(float* d, const uint32_t* a, uint64_t db) {
  asm volatile("wgmma.mma_async.sync.aligned.m64n48k16.f32.bf16.bf16 {%0, %1, %2, %3, %4, %5, %6, %7, %8, %9, %10, %11, %12, %13, %14, %15, %16, %17, %18, %19, %20, %21, %22, %23}, {%24,%25,%26,%27}, %28, 1, 1, 1, 0;"
    : "+f"(d[0]), "+f"(d[1]), "+f"(d[2]), "+f"(d[3]), "+f"(d[4]), "+f"(d[5]), "+f"(d[6]), "+f"(d[7]), "+f"(d[8]), "+f"(d[9]), "+f"(d[10]), "+f"(d[11]), "+f"(d[12]), "+f"(d[13]), "+f"(d[14]), "+f"(d[15]), "+f"(d[16]), "+f"(d[17]), "+f"(d[18]), "+f"(d[19]), "+f"(d[20]), "+f"(d[21]), "+f"(d[22]), "+f"(d[23])
    : "r"(a[0]), "r"(a[1]), "r"(a[2]), "r"(a[3]), "l"(db));
}
template <> __device__ __forceinline__ void cvm<64, 1>(float* d, const uint32_t* a, uint64_t db) {
  asm volatile("wgmma.mma_async.sync.aligned.m64n64k16.f32.bf16.bf16 {%0, %1, %2, %3, %4, %5, %6, %7, %8, %9, %10, %11, %12, %13, %14, %15, %16, %17, %18, %19, %20, %21, %22, %23, %24, %25, %26, %27, %28, %29, %30, %31}, {%32,%33,%34,%35}, %36, 1, 1, 1, 0;"
    : "+f"(d[0]), "+f"(d[1]), "+f"(d[2]), "+f"(d[3]), "+f"(d[4]), "+f"(d[5]), "+f"(d[6]), "+f"(d[7]), "+f"(d[8]), "+f"(d[9]), "+f"(d[10]), "+f"(d[11]), "+f"(d[12]), "+f"(d[13]), "+f"(d[14]), "+f"(d[15]), "+f"(d[16]), "+f"(d[17]), "+f"(d[18]), "+f"(d[19]), "+f"(d[20]), "+f"(d[21]), "+f"(d[22]), "+f"(d[23]), "+f"(d[24]), "+f"(d[25]), "+f"(d[26]), "+f"(d[27]), "+f"(d[28]), "+f"(d[29]), "+f"(d[30]), "+f"(d[31])
    : "r"(a[0]), "r"(a[1]), "r"(a[2]), "r"(a[3]), "l"(db));
}

__device__ __forceinline__ void conv_lda(uint32_t (&a)[32], uint32_t ab) {
#pragma unroll
  for (int i = 0; i < 8; i++) {
    a[4 * i] = lds32(ab + 256 * i); a[4 * i + 1] = lds32(ab + 128 + 256 * i); a[4 * i + 2] = lds32(ab + 16 + 256 * i); a[4 * i + 3] = lds32(ab + 144 + 256 * i);
  }
}
template <int S, int I0, int I = I0> __device__ __forceinline__ void conv_step(float (&d)[32], const uint32_t (&a)[32], uint64_t db) {
  constexpr int R = 256 - 16 * I - 64 * S;
  if constexpr (R > 0) cvm<(R < 64 ? R : 64), I == 0 ? 0 : 1>(d, &a[4 * (I - I0)], db + 16 * I + 64 * S);
  if constexpr (I < I0 + 7) conv_step<S, I0, I + 1>(d, a, db);
}
template <int S> __device__ __forceinline__ void conv_epi_a(const float (&d)[32], float (&ch)[2], float (&cr)[2], uint32_t xw, bool bw) {
  constexpr int H = (S & 1) * 2048;
  const float r0 = d[0] + d[6], r1 = d[1] + d[7];
  sts64f(xw + H + (bw ? 8 * 256 : 0), bw ? cr[0] : r0, bw ? cr[1] : r1);
  cr[0] = r0; cr[1] = r1;
#pragma unroll
  for (int q = 7; q > 0; q--) sts64f(xw + H + q * 256, d[4 * q] + (q == 7 ? ch[0] : d[4 * q + 6]), d[4 * q + 1] + (q == 7 ? ch[1] : d[4 * q + 7]));
  ch[0] = d[2]; ch[1] = d[3];
}
template <int S> __device__ __forceinline__ void conv_epi_b(uint32_t xr, uint32_t ys, uint32_t ks, uint32_t dd) {
  float2 p[4][4];
  uint32_t k0[4], k1[4];
#pragma unroll
  for (int q = 0; q < 4; q++)
#pragma unroll
    for (int w = 0; w < 4; w++) p[q][w] = lds64f(xr + (q >> 1) * 2048 + w * 4096 + (q & 1) * 256);
#pragma unroll
  for (int q = 0; q < 4; q++) { k0[q] = lds16(ks + 1024 * (S + (q >> 1)) + 128 * (q & 1) - 16); k1[q] = lds16(ks + 1024 * (S + (q >> 1)) + 128 * (q & 1)); }
#pragma unroll
  for (int q = 0; q < 4; q++) {
    const float ya = (p[q][0].x + p[q][1].x) + (p[q][2].x + p[q][3].x), yb = (p[q][0].y + p[q][1].y) + (p[q][2].y + p[q][3].y);
    const uint32_t r = hadd2u(pack2(ya, yb), hmul2u(k0[q] | (k1[q] << 16), dd));
    sts16(ys - 1024 * (S + (q >> 1)) - 128 * (q & 1) + 16, (uint16_t)(r & 0xFFFF));
    sts16(ys - 1024 * (S + (q >> 1)) - 128 * (q & 1), (uint16_t)(r >> 16));
  }
}

#define EXIT_COUNT() do { if (atomicAdd(&g_cnt[CNT_EXIT], 1) == 128 * 3 - 1) { for (int _i = 0; _i < NCNT; _i += 32) g_cnt[_i] = 0; g_epoch = g_epoch + 1; } } while (0)

struct Params {
  const bf16 *q, *k, *v, *shift, *h, *dvec, *x, *wqkv, *wo;
  bf16* out;
};

__global__ void __cluster_dims__(2, 1, 1) __launch_bounds__(512, 1)
fused_kernel(const __grid_constant__ CUtensorMap tmX, const __grid_constant__ CUtensorMap tmW64, const __grid_constant__ CUtensorMap tmW16,
             const __grid_constant__ CUtensorMap tmWo, const __grid_constant__ CUtensorMap tmOld, const __grid_constant__ CUtensorMap tmOst,
             const __grid_constant__ CUtensorMap tmOut, const __grid_constant__ CUtensorMap tmXr, const Params P) {
  extern __shared__ uint8_t smem_raw[];
  const uint32_t sb = (s2u(smem_raw) + 1023) & ~1023u;
  const uint32_t bars = sb + BAR_OFF;
  const int tid = threadIdx.x, warp = __shfl_sync(~0u, tid >> 5, 0), lane = tid & 31, wg = warp >> 2;
  const int b = blockIdx.x, rank = b & 1;
  const int tt = (b >> 5) * 4 + (b & 3), hg = ((b >> 4) & 1) * 4 + ((b >> 2) & 3), par = tt >> 3, rt = tt & 7, tid8 = tt * 8 + hg;
#define BAR(i) (bars + 8 * (i))
  constexpr int STW = 0;
  if (warp == 12) {
    if (lane == 0) {
      STAMP(0);
      for (int i = 0; i < NSX; i++) { mbar_init(BAR(B_FX + i), 1); mbar_init(BAR(B_EX + i), 8); }
      for (int i = 0; i < NSW; i++) { mbar_init(BAR(B_FW + i), 1); mbar_init(BAR(B_EW + i), 16); }
      asm volatile("fence.mbarrier_init.release.cluster;" ::: "memory");
      fence_async_s();
      for (int i = 0; i < NSW; i++) mbar_expect(BAR(B_FW + i), WSL);
      mbar_expect(BAR(B_FX), 16384);
      tma3(sb + WR_OFF, &tmW64, hg * 80, 0, 0, BAR(B_FW));
      tma3(sb, &tmX, 0, par, rt * 128, BAR(B_FX));
      tma3(sb + WR_OFF + 12288, &tmW16, hg * 80 + 64, 0, 0, BAR(B_FW));
    }
  } else if (warp == 13) {
    if (lane == 0) {
      for (int i = 0; i < NS2; i++) { mbar_init(BAR(B_FULL2 + i), 1); mbar_init(BAR(B_EMPTY2 + i), 8); }
      for (int i = 0; i < 5; i++) { mbar_init(BAR(B_XH + i), i ? 5 : 7); mbar_init(BAR(B_YDONE + i), 4); mbar_init(BAR(B_PST + i), 4); }
      mbar_init(BAR(B_OST), 8); mbar_init(BAR(B_XFREE), 16);
      asm volatile("fence.mbarrier_init.release.cluster;" ::: "memory");
      fence_async_s();
    }
  }
  asm volatile("barrier.cluster.arrive.relaxed.aligned;\nbarrier.cluster.wait.aligned;" ::: "memory");

  if (wg < 3) {
  asm volatile("setmaxnreg.inc.sync.aligned.u32 160;");
  const int g = lane >> 2, t = lane & 3, wq = warp & 3;
  if (wg < 2) {
    constexpr int STW = 1;
    uint32_t qa[10][2];
    const uint32_t tag = *reinterpret_cast<volatile unsigned*>(&g_epoch) + 1;
    {
      float a192[96], a48[24];
      int ws = 0, wph = 0;
#pragma unroll 1
      for (int h = 0; h < 20; h++) {
        const int xs = (h >> 1) & 3;
        if (!(h & 1)) mbar_wait(BAR(B_FX + xs), (h >> 3) & 1);
        mbar_wait(BAR(B_FW + ws), wph);
        if (h == 0) { STAMP(1); CSTAMP(30); }
        if (wg == 0 && !(h & 1)) STAMP(32 + (h >> 1));
        const uint64_t da = mkdesc(sb + xs * 16384 + wg * 8192 + (h & 1) * 64, 16, 1024, 1);
        const uint64_t db = mkdesc(sb + WR_OFF + ws * WSL, 4096, 1024, 1);
        const uint64_t dc = mkdesc(sb + WR_OFF + ws * WSL + 12288, 1024, 256, 3);
        WG_FENCE();
        wg192(a192, da, db, h);
        wg48(a48, da, dc, h);
        wg192(a192, da + 2, db + 128, 1);
        wg48(a48, da + 2, dc + 32, 1);
        WG_COMMIT();
        if (h > 0) {
          WG_WAIT(1);
          if (h <= 20 - NSW && lane < 2) mbar_arrive_cl(BAR(B_EW + (ws == 0 ? NSW - 1 : ws - 1)), lane);
          if (!(h & 1) && h <= 2 * (10 - NSX) && lane == 2) mbar_arrive(BAR(B_EX + ((xs + 3) & 3)));
        }
        if (++ws == NSW) { ws = 0; wph ^= 1; }
      }
      WG_WAIT(0);
      STAMP(2 + wg);
      bar_sync(1, 256);
      const uint32_t kvw = sb + KV_OFF + (8 + 16 * warp + (lane & 7) + 8 * ((lane >> 3) & 1)) * KV_PITCH + (lane >> 4) * 16;
#pragma unroll
      for (int p = 1; p < 3; p++) {
#pragma unroll
        for (int jb = 0; jb < 10; jb += 2) {
          const float* A = jb < 8 ? &a192[(p * 8 + jb) * 4] : &a48[(p * 2) * 4];
          uint32_t r0 = pack2(A[0], A[1]), r1 = pack2(A[2], A[3]), r2 = pack2(A[4], A[5]), r3 = pack2(A[6], A[7]);
          stsm4(kvw + (p - 1) * 160 + jb * 16, r0, r1, r2, r3);
          if (warp == 7 && rt < 7) {
            uint2* hp = g_halo + tid8 * 640 + ((p - 1) * 10 + jb) * 32 + lane;
            asm volatile("st.relaxed.gpu.global.v2.u32 [%0], {%1, %2};" ::"l"(hp), "r"(r1), "r"(tag) : "memory");
            asm volatile("st.relaxed.gpu.global.v2.u32 [%0], {%1, %2};" ::"l"(hp + 32), "r"(r3), "r"(tag) : "memory");
          }
        }
      }
#pragma unroll
      for (int jb = 0; jb < 10; jb++) {
        const float* A = jb < 8 ? &a192[jb * 4] : &a48[(jb - 8) * 4];
        qa[jb][0] = pack2(A[0], A[1]); qa[jb][1] = pack2(A[2], A[3]);
      }
    }
    bar_sync(1, 256);
    STAMP(4 + wg);
    {
      const uint32_t l1 = sb + KV_OFF + (16 * warp + (lane & 7) + 8 * (lane >> 4)) * KV_PITCH + ((lane >> 3) & 1) * 16;
      const uint32_t l2 = sb + KV_OFF + (16 * warp + 16 + (lane & 7)) * KV_PITCH + (lane >> 3) * 16;
      uint32_t f[3][10];
#pragma unroll
      for (int jb = 0; jb < 10; jb += 2) ldsm4(l1 + jb * 16, f[0][jb], f[0][jb + 1], f[1][jb], f[1][jb + 1]);
      ldsm4(l2, f[2][0], f[2][1], f[2][2], f[2][3]);
      ldsm4(l2 + 64, f[2][4], f[2][5], f[2][6], f[2][7]);
      ldsm2(l2 + 128, f[2][8], f[2][9]);
      uint32_t hv[10];
      if (warp == 0) {
#pragma unroll
        for (int j = 0; j < 10; j++) { f[0][j] = 0u; hv[j] = 0u; }
        if (rt > 0) {
          const uint2* hp = g_halo + (tid8 - 8) * 640 + lane;
          for (int it = 0; it < (1 << 17); it++) {
            uint32_t ok = 1;
#pragma unroll
            for (int j = 0; j < 20; j++) {
              uint32_t v, tg;
              asm volatile("ld.relaxed.gpu.global.v2.u32 {%0, %1}, [%2];" : "=r"(v), "=r"(tg) : "l"(hp + j * 32) : "memory");
              if (j < 10) f[0][j] = v; else hv[j - 10] = v;
              ok &= (tg == tag);
            }
            if (__all_sync(~0u, ok)) break;
          }
        }
      }
      const uint32_t mlo = t < 2 ? 0xFFFFFFFFu : 0u;
      const bool sel0 = 2 * t >= g + 1, sel1 = 2 * t + 1 >= g + 1;
      const uint32_t pm = (sel0 ? 0xFFFFu : 0u) | (sel1 ? 0xFFFF0000u : 0u);
      const bool edge = (rt == 0 && warp == 0);
      uint32_t pa[4][2];
      float s[4][3][4];
#pragma unroll
      for (int h = 0; h < 4; h++) {
        const int j16 = (h >> 1) * 5 + (h & 1) * 3;
#pragma unroll
        for (int n = 0; n < 3; n++) {
          s[h][n][0] = s[h][n][1] = s[h][n][2] = s[h][n][3] = 0.f;
          mma16(s[h][n], qa[j16][0], qa[j16][1], qa[j16 + 1][0], qa[j16 + 1][1], f[n][j16], f[n][j16 + 1]);
        }
      }
#pragma unroll
      for (int h = 0; h < 4; h++) {
        const int j8 = (h >> 1) * 5 + 2;
        const uint32_t hm = (h & 1) ? ~mlo : mlo;
#pragma unroll
        for (int n = 0; n < 3; n++) mma8(s[h][n], qa[j8][0] & hm, qa[j8][1] & hm, f[n][j8]);
      }
#pragma unroll
      for (int jb = 0; jb < 10; jb += 2) ldsm4t(l1 + 160 + jb * 16, f[0][jb], f[0][jb + 1], f[1][jb], f[1][jb + 1]);
      ldsm4t(l2 + 160, f[2][0], f[2][1], f[2][2], f[2][3]);
      ldsm4t(l2 + 160 + 64, f[2][4], f[2][5], f[2][6], f[2][7]);
      ldsm2t(l2 + 160 + 128, f[2][8], f[2][9]);
      if (warp == 0) {
#pragma unroll
        for (int j = 0; j < 10; j++) f[0][j] = movtrans(hv[j]);
      }
      float e0[8], e1[8], mx[8];
#pragma unroll
      for (int u = 0; u < 8; u++) {
        const int h = u >> 1, hf = u & 1;
        const float sc = 0.22360679774997896f;
        const uint32_t p = pack2(sel0 ? s[h][hf][2 * hf] : s[h][hf + 1][2 * hf], sel1 ? s[h][hf][2 * hf + 1] : s[h][hf + 1][2 * hf + 1]);
        const uint32_t p2 = pack2(lo2f(p) * sc, hi2f(p) * sc);
        e0[u] = lo2f(p2); e1[u] = hi2f(p2);
        if (hf == 0 && edge) { if (sel0) e0[u] = -1e9f; if (sel1) e1[u] = -1e9f; }
        mx[u] = fmaxf(e0[u], e1[u]);
      }
#pragma unroll
      for (int u = 0; u < 8; u++) mx[u] = fmaxf(mx[u], __shfl_xor_sync(~0u, mx[u], 1));
#pragma unroll
      for (int u = 0; u < 8; u++) mx[u] = fmaxf(mx[u], __shfl_xor_sync(~0u, mx[u], 2));
#pragma unroll
      for (int u = 0; u < 8; u++) {
        e0[u] = ex2f((e0[u] - mx[u]) * 1.4426950408889634f); e1[u] = ex2f((e1[u] - mx[u]) * 1.4426950408889634f);
        mx[u] = e0[u] + e1[u];
      }
#pragma unroll
      for (int u = 0; u < 8; u++) mx[u] += __shfl_xor_sync(~0u, mx[u], 1);
#pragma unroll
      for (int u = 0; u < 8; u++) mx[u] += __shfl_xor_sync(~0u, mx[u], 2);
#pragma unroll
      for (int u = 0; u < 8; u++) { const float r = rcpf(mx[u]); pa[u >> 1][u & 1] = pack2(e0[u] * r, e1[u] * r); }
      uint32_t ob[10][2];
#pragma unroll
      for (int h = 0; h < 4; h++) {
        const int j0 = (h >> 1) * 5 + (h & 1) * 2;
#pragma unroll
        for (int jj = 0; jj < 3; jj++) {
          const int jb = j0 + jj;
          float o[4] = {0.f, 0.f, 0.f, 0.f};
          mma16(o, pa[h][0] & pm, 0u, pa[h][0] & ~pm, pa[h][1] & pm, f[0][jb], f[1][jb]);
          mma8(o, 0u, pa[h][1] & ~pm, f[2][jb]);
          uint32_t u0 = pack2(o[0], o[1]), u1 = pack2(o[2], o[3]);
          if ((h & 1) && jj == 0) { ob[jb][0] = t < 2 ? ob[jb][0] : u0; ob[jb][1] = t < 2 ? ob[jb][1] : u1; }
          else { ob[jb][0] = u0; ob[jb][1] = u1; }
        }
      }
      const uint32_t os = sb + OST_OFF + warp * 2560;
      const uint32_t ow = os + ((lane & 7) + 8 * ((lane >> 3) & 1)) * 160 + (lane >> 4) * 16;
#pragma unroll
      for (int jb = 0; jb < 10; jb += 2) stsm4(ow + jb * 16, ob[jb][0], ob[jb][1], ob[jb + 1][0], ob[jb + 1][1]);
      fence_async_s();
      __syncwarp();
      if (lane == 0) mbar_arrive(BAR(B_OST));
    }
    STAMP(6 + wg); CSTAMP(31);
  } else {
    const int wi = warp & 3, rh = lane & 1, s0 = 16 * b + 8 * rh, cp0 = 16 * wi + (lane >> 1);
    mbar_wait(BAR(B_FW + KV_SLOT), 0);
    {
      const int o0 = (tid & 127) * 16;
      const char* kg = reinterpret_cast<const char*>(P.k) + (16 * b - 3) * 1280;
      const char* vg = reinterpret_cast<const char*>(P.v) + (16 * b) * 1280;
#pragma unroll
      for (int i = 0; i < 7; i++) {
        const int o = o0 + i * 2048;
        if (o < 14080) {
          if (b > 0 || o >= 3840) cp16(sb + KS_OFF + o, kg + o);
          cp16(sb + KS_OFF + KS_H + o, kg + 10240 + o);
        }
        if (i >= 4 && o < 8192 + 5120) cp16(sb + SH_OFF + o - 8192, reinterpret_cast<const char*>(P.shift) + o - 8192);
        asm volatile("cp.async.commit_group;\ncp.async.wait_group %0;" ::"n"(KV_FL) : "memory");
        if (i < 5) {
          cp16(sb + VS_OFF + o, vg + o); cp16(sb + VS_OFF + VS_H + o, vg + 10240 + o);
          asm volatile("cp.async.commit_group;\ncp.async.wait_group %0;" ::"n"(KV_FL) : "memory");
        }
      }
      STAMP(10);
      asm volatile("cp.async.wait_all;" ::: "memory");
    }
    const int j0 = wi * 64 + lane;
    uint4 hw[5][2]; uint32_t hprev[5];
#pragma unroll
    for (int c = 0; c < 5; c++) {
      const uint4* hp = reinterpret_cast<const uint4*>(P.h + (size_t)(128 * c + b) * 2048) + j0;
      hw[c][0] = __ldg(hp); hw[c][1] = __ldg(hp + 32);
      hprev[c] = (lane == 0 && j0 > 0) ? __ldg(reinterpret_cast<const uint32_t*>(hp) - 1) : 0u;
    }
    const uint32_t dv = (wi == 0 && lane < 5) ? (uint32_t)__ldg(reinterpret_cast<const unsigned short*>(P.dvec) + 128 * lane + b) * 0x10001u : 0u;
    bar_sync(4, 128);
    STAMP(19);
    uint32_t kk[2][11], kv[2][8];
    uint4 sw[2];
    const uint32_t ka = sb + KS_OFF + rh * KS_H + cp0 * 4, va = sb + VS_OFF + rh * VS_H + cp0 * 4, sa = sb + SH_OFF + cp0 * 16;
#pragma unroll
    for (int j = -1; j < 5; j++) {
      if (j < 4) {
        const int n = (j + 1) & 1;
        asm volatile("ld.shared.v4.u32 {%0,%1,%2,%3}, [%4];" : "=r"(sw[n].x), "=r"(sw[n].y), "=r"(sw[n].z), "=r"(sw[n].w) : "r"(sa + (j + 1) * 1024) : "memory");
#pragma unroll
        for (int r = 0; r < 11; r++) kk[n][r] = lds32(ka + r * 1280 + (j + 1) * 256);
#pragma unroll
        for (int r = 0; r < 8; r++) kv[n][r] = lds32(va + r * 1280 + (j + 1) * 256);
      }
      if (j >= 0) {
        const int n = j & 1;
        const uint4 w = sw[n];
        const uint32_t w0 = __byte_perm(w.x, w.z, 0x5410), w1 = __byte_perm(w.x, w.z, 0x7632);
        const uint32_t w2 = __byte_perm(w.y, w.w, 0x5410), w3 = __byte_perm(w.y, w.w, 0x7632);
        if (s0 == 0) kk[n][0] = kk[n][1] = kk[n][2] = 0u;
        uint32_t o[8];
#pragma unroll
        for (int r = 0; r < 8; r++) {
          uint32_t a = hmul2u(kk[n][r], w3);
          a = hadd2u(a, hmul2u(kk[n][r + 1], w2));
          a = hadd2u(a, hmul2u(kk[n][r + 2], w1));
          a = hadd2u(a, hmul2u(kk[n][r + 3], w0));
          o[r] = hmul2u(a, kv[n][r]);
        }
        const uint32_t dst = sb + XC2_OFF + j * 4096 + cp0 * 64 + (1 - rh) * 16, fl = (lane & 4) * 8;
        const uint32_t p0 = fl ? 0x7632 : 0x5410, p1 = fl ? 0x5410 : 0x7632;
        asm volatile("st.shared.v4.u32 [%0], {%1,%2,%3,%4};" ::"r"(dst + fl), "r"(__byte_perm(o[7], o[6], p0)), "r"(__byte_perm(o[5], o[4], p0)),
                     "r"(__byte_perm(o[3], o[2], p0)), "r"(__byte_perm(o[1], o[0], p0)) : "memory");
        asm volatile("st.shared.v4.u32 [%0], {%1,%2,%3,%4};" ::"r"(dst + 32 - fl), "r"(__byte_perm(o[7], o[6], p1)), "r"(__byte_perm(o[5], o[4], p1)),
                     "r"(__byte_perm(o[3], o[2], p1)), "r"(__byte_perm(o[1], o[0], p1)) : "memory");
        fence_async_s();
        __syncwarp();
        if (lane == 0) mbar_arrive(BAR(B_PST + j));
      }
    }
    STAMP(42);
    bar_sync(4, 128);
    if (wi == 0 && lane < 5) {
      const uint32_t cb = sb + CH_OFF + lane * CH_SZ;
      asm volatile("st.shared.u32 [%0], %1;" ::"r"(cb + DV_OFF), "r"(dv) : "memory");
      asm volatile("st.shared.v4.u32 [%0], {%1,%1,%1,%1};" ::"r"(cb + HB_OFF - 16), "r"(0) : "memory");
      asm volatile("st.shared.v4.u32 [%0], {%1,%1,%1,%1};" ::"r"(cb + HA_OFF - 16), "r"(0) : "memory");
      asm volatile("st.shared.v4.u32 [%0], {%1,%1,%1,%1};" ::"r"(cb + XR_OFF + 4096), "r"(0) : "memory");
      fence_async_s();
    }
#pragma unroll
    for (int c = 0; c < 5; c++) {
      const uint32_t cb = sb + CH_OFF + c * CH_SZ + j0 * 16;
      uint32_t prev = hprev[c];
#pragma unroll
      for (int i = 0; i < 2; i++) {
        const uint4 w = hw[c][i];
        uint32_t up = __shfl_up_sync(~0u, w.w, 1);
        if (lane == 0) up = prev;
        prev = __shfl_sync(~0u, w.w, 31);
        asm volatile("st.shared.v4.u32 [%0], {%1,%2,%3,%4};" ::"r"(cb + HA_OFF + 512 * i), "r"(w.x), "r"(w.y), "r"(w.z), "r"(w.w) : "memory");
        asm volatile("st.shared.v4.u32 [%0], {%1,%2,%3,%4};" ::"r"(cb + HB_OFF + 512 * i), "r"(__byte_perm(up, w.x, 0x5432)),
                     "r"(__byte_perm(w.x, w.y, 0x5432)), "r"(__byte_perm(w.y, w.z, 0x5432)), "r"(__byte_perm(w.z, w.w, 0x5432)) : "memory");
      }
    }
    __syncwarp();
    if (lane < 5) mbar_arrive(BAR(B_XH + lane));
    STAMP(25);
  }
  {
    constexpr int STW = 1;
    const uint32_t xb = sb + (wg == 2 ? XC2_OFF : XCH_OFF + wg * 16384);
    const bool bw = t < wq;
    const uint32_t xw = xb + wq * 4096 - (bw ? 256 : 0) + (g * 4 + ((t - wq) & 3)) * 8;
    const uint32_t xr = xb + wq * 512 + lane * 8;
    const int sb0 = g + 16 * (127 - t - 8 * wq);
#pragma unroll 1
    for (int c = wg == 2 ? 0 : 3 - wg; c < 5; c += (c == 0 ? 1 : 3)) {
      const uint32_t cb = sb + CH_OFF + c * CH_SZ;
      mbar_wait(BAR(B_XH + c), 0);
      STAMP(54 + c);
      const uint32_t ab = cb + ((g & 1) ? HA_OFF : HB_OFF) + 4 * ((g >> 1) - 3 + 8 * wq + t);
      const uint64_t db = mkdesc(cb + XR_OFF, 16, 128, 0);
      uint32_t a[32];
      float dA[32], dB[32];
      conv_lda(a, ab);
      const uint32_t ys = cb + HB_OFF + 2 * sb0, ks = cb + XR_OFF + 2 * (2047 - sb0);
      const uint32_t dd = lds32(cb + DV_OFF);
      float ch[2] = {0.f, 0.f}, cr[2] = {0.f, 0.f};
      WG_FENCE();
      conv_step<3, 0>(dA, a, db);
      conv_step<2, 0>(dB, a, db);
      WG_COMMIT();
      bar_sync(2 + wg, 128);
      WG_WAIT(0);
      conv_epi_a<3>(dA, ch, cr, xw, bw);
      conv_epi_a<2>(dB, ch, cr, xw, bw);
      WG_FENCE();
      conv_step<1, 0>(dA, a, db);
      conv_step<0, 0>(dB, a, db);
      WG_COMMIT();
      WG_WAIT(0);
      conv_lda(a, ab + 2048);
      WG_FENCE();
      conv_step<1, 8>(dA, a, db);
      conv_step<0, 8>(dB, a, db);
      WG_COMMIT();
      bar_sync(2 + wg, 128);
      WG_WAIT(0);
      conv_epi_b<2>(xr, ys, ks, dd);
      bar_sync(2 + wg, 128);
      conv_epi_a<1>(dA, ch, cr, xw, bw);
      conv_epi_a<0>(dB, ch, cr, xw, bw);
      bar_sync(2 + wg, 128);
      conv_epi_b<0>(xr, ys, ks, dd);
      fence_async_s();
      __syncwarp();
      if (lane == 0) mbar_arrive(BAR(B_YDONE + c));
      STAMP(59 + c);
    }
    if (wg < 2 && lane < 2) mbar_arrive_cl(BAR(B_XFREE), lane);
    if (wg == 0) {
      const int s0 = 16 * b + 8 * (lane & 1), cp0 = 16 * wq + (lane >> 1);
      uint32_t* op = reinterpret_cast<uint32_t*>(P.out) + (size_t)s0 * 640 + cp0;
      const uint32_t* qp = reinterpret_cast<const uint32_t*>(P.q) + (size_t)s0 * 320 + cp0;
      const uint4* yp = reinterpret_cast<const uint4*>(g_y + (size_t)(2 * cp0) * 2048 + s0);
      uint32_t qv[5][8];
#pragma unroll
      for (int j = 0; j < 5; j++)
#pragma unroll
        for (int r = 0; r < 8; r++) qv[j][r] = __ldg(qp + r * 320 + 64 * j);
#pragma unroll
      for (int j0 = 0; j0 < 5; j0 += (j0 ? 3 : 2)) {
        const int n = j0 ? 3 : 2;
        if (tid < n) wait_ge(&g_cnt[CNT_Y(j0 + tid)], 128);
        __syncwarp();
        bar_sync(2, 128);
        if (j0 == 2) STAMP(20);
        uint4 ya[3], yb[3];
#pragma unroll
        for (int u = 0; u < n; u++) { ya[u] = __ldcg(yp + (j0 + u) * 32768); yb[u] = __ldcg(yp + (j0 + u) * 32768 + 256); }
#pragma unroll
        for (int u = 0; u < n; u++) {
          const uint32_t A[4] = {ya[u].x, ya[u].y, ya[u].z, ya[u].w}, B[4] = {yb[u].x, yb[u].y, yb[u].z, yb[u].w};
#pragma unroll
          for (int r = 0; r < 4; r++) {
            op[(2 * r) * 640 + 64 * (j0 + u)] = hmul2u(qv[j0 + u][2 * r], __byte_perm(A[r], B[r], 0x5410));
            op[(2 * r + 1) * 640 + 64 * (j0 + u)] = hmul2u(qv[j0 + u][2 * r + 1], __byte_perm(A[r], B[r], 0x7632));
          }
        }
      }
      if (tid == 0) { EXIT_COUNT(); }
      STAMP(21);
    }
  }
  if (wg == 1) {
    constexpr int STW = 1;
    float acc0[40], acc1[40];
    int slot = 0, ph = 0;
#pragma unroll 1
    for (int kb = 0; kb < 10; kb++) {
      mbar_wait(BAR(B_FULL2 + slot), ph);
      STAMP(44 + kb);
      const uint32_t st = sb + slot * ST2;
      const uint64_t da = mkdesc(st, 16, 1024, 1);
      const uint64_t db = mkdesc(st + 16384, 2048, 512, 2);
      WG_FENCE();
#pragma unroll
      for (int k = 0; k < 4; k++) {
        wg80(acc0, da + k * 2, db + (k & 1) * 64 + (k >> 1) * 384, kb | k);
        wg80(acc1, da + 512 + k * 2, db + (k & 1) * 64 + (k >> 1) * 384, kb | k);
      }
      WG_COMMIT();
      if (kb > 0) {
        WG_WAIT(1);
        if (kb <= 10 - NS2 && lane < 2) mbar_arrive_cl(BAR(B_EMPTY2 + (slot == 0 ? NS2 - 1 : slot - 1)), lane);
      }
      if (kb == B2_KW) mbar_wait(BAR(B_YDONE + 4), 0);
      if (++slot == NS2) { slot = 0; ph ^= 1; }
    }
    WG_WAIT(0);
    STAMP(14);
    bar_sync(3, 128);
    const uint32_t os = sb + 2 * ST2 + wq * 5120;
    const uint32_t ow = os + ((lane & 7) + 8 * ((lane >> 3) & 1)) * 160 + (lane >> 4) * 16;
#pragma unroll
    for (int jb = 0; jb < 10; jb += 2) {
      stsm4(ow + jb * 16, pack2(acc0[4 * jb], acc0[4 * jb + 1]), pack2(acc0[4 * jb + 2], acc0[4 * jb + 3]),
            pack2(acc0[4 * jb + 4], acc0[4 * jb + 5]), pack2(acc0[4 * jb + 6], acc0[4 * jb + 7]));
      stsm4(ow + 2560 + jb * 16, pack2(acc1[4 * jb], acc1[4 * jb + 1]), pack2(acc1[4 * jb + 2], acc1[4 * jb + 3]),
            pack2(acc1[4 * jb + 4], acc1[4 * jb + 5]), pack2(acc1[4 * jb + 6], acc1[4 * jb + 7]));
    }
    fence_async_s();
    __syncwarp();
    if (lane == 0) {
      tma3_st(&tmOut, 640 + hg * 80, par, rt * 128 + wq * 16, os);
      tma3_st(&tmOut, 640 + hg * 80, par, rt * 128 + 64 + wq * 16, os + 2560);
      bulk_commit();
      asm volatile("cp.async.bulk.wait_group.read 0;" ::: "memory");
    }
    STAMP(16);
  }
  } else {
    asm volatile("setmaxnreg.dec.sync.aligned.u32 32;");
    if (warp == 12) {
      if (lane == 0) {
#pragma unroll 1
        for (int h = 0; h < 20; h++) {
          const int ws = h % NSW;
          if (h >= NSW) {
            mbar_wait(BAR(B_EW + ws), ((h / NSW) - 1) & 1);
            mbar_expect(BAR(B_FW + ws), WSL);
          }
          if (h && (h & 1) == rank) {
            tma3mc(sb + WR_OFF + ws * WSL, &tmW64, hg * 80, h * 32, 0, BAR(B_FW + ws));
            tma3mc(sb + WR_OFF + ws * WSL + 12288, &tmW16, hg * 80 + 64, h * 32, 0, BAR(B_FW + ws));
          }
          const int kb = (h + 1) >> 1;
          if ((h & 1) && kb < 10) {
            if (kb >= NSX) mbar_wait(BAR(B_EX + (kb & 3)), ((kb >> 2) - 1) & 1);
            mbar_expect(BAR(B_FX + (kb & 3)), 16384);
            tma3(sb + (kb & 3) * 16384, &tmX, kb * 64, par, rt * 128, BAR(B_FX + (kb & 3)));
          }
        }
        wait_ge(&g_cnt[CNT_O(tt)], 8);
        wait_ge(&g_cnt[CNT_O(tt ^ 1)], 8);
        fence_async_g();
        STAMP(22);
        for (int kb = 0; kb < 10; kb++) {
          const int slot = kb % NS2;
          if (kb >= NS2) mbar_wait(BAR(B_EMPTY2 + slot), 0);
          if (kb == 4) mbar_wait(BAR(B_XFREE), 0);
          uint32_t st = sb + slot * ST2, fb = BAR(B_FULL2 + slot);
          mbar_expect(fb, ST2);
          for (int a = 0; a < 3; a++) tma2mc(st + 16384 + rank * 6144 + a * 2048, &tmWo, hg * 80 + a * 32, kb * 64 + rank * 32, fb);
          tma2(st, &tmOld, kb * 64, tt * 128, fb);
        }
        EXIT_COUNT();
      }
    } else {
      constexpr int STW = 1;
      if (warp > 13) {
        __nanosleep(PF0_NS);
        const char* xp = reinterpret_cast<const char*>(P.x) + (16 * b + (lane >> 1)) * 1280 + (lane & 1) * 128;
        if (warp == 14) asm volatile("prefetch.global.L2 [%0];" ::"l"(xp + 384) : "memory");
        else pf_lines(reinterpret_cast<const char*>(P.wqkv) + 160 * 3840 + b * 4864, 4864, lane);
        mbar_wait(BAR(B_FW + PFA_SLOT), 0);
        if (warp == 14) asm volatile("prefetch.global.L2 [%0];" ::"l"(xp + 640) : "memory");
        else pf_lines(reinterpret_cast<const char*>(P.wqkv) + 320 * 3840 + b * 3840, 3840, lane);
        mbar_wait(BAR(B_FW + PF1_SLOT), 1);
        if (warp == 14) { for (int o = 896; o + (lane & 1) * 128 < 1280; o += 256) asm volatile("prefetch.global.L2 [%0];" ::"l"(xp + o) : "memory"); }
        else pf_lines(reinterpret_cast<const char*>(P.wqkv) + 448 * 3840 + b * 5760, 5760, lane);
        { constexpr int STW = 2; STAMP(9); }
        if (lane == 0) {
#pragma unroll 1
          for (int j = 15 - warp; j < 5; j += 2) {
            mbar_wait(BAR(B_PST + j), 0);
            tma2_st(&tmXr, 2032 - 16 * b, 128 * j, sb + XC2_OFF + j * 4096);
            bulk_commit(); bulk_wait0(); fence_async_g();
            red_relaxed(&g_cnt[CNT_PRE(j)], 1);
            { constexpr int STW = 3; if (j == 0) STAMP(18); if (j == 4) STAMP(11); }
          }
          mbar_arrive(BAR(B_XH));
        }
      }
      if (warp == 13) {
        mbar_wait(BAR(B_PST + 4), 0);
        bool todo = lane < 5;
#pragma unroll 1
        for (int it = 0; it < (1 << 16) && __any_sync(~0u, todo); it++) {
          if (todo) {
            unsigned v;
            asm volatile("ld.acquire.gpu.global.u32 %0, [%1];" : "=r"(v) : "l"(&g_cnt[CNT_PRE(lane)]) : "memory");
            if (v >= 128) {
              STAMP(23);
              fence_async_g();
              mbar_expect(BAR(B_XH + lane), 4096);
              bulk_ld(sb + CH_OFF + lane * CH_SZ + XR_OFF, g_xr + (size_t)(128 * lane + b) * 2048, 4096, BAR(B_XH + lane));
              todo = false;
            }
          }
          __nanosleep(40);
        }
        if (lane == 0) { EXIT_COUNT(); }
        __syncwarp();
        pf_lines(reinterpret_cast<const char*>(P.wo) + b * 6400, 6400, lane);
        pf_lines(P.q + (size_t)(16 * b) * 640, 20480, lane);
      } else if (warp == 14 && lane == 0) {
        constexpr int STW = 2;
        mbar_wait(BAR(B_OST), 0);
        STAMP(28);
        tma2_st(&tmOst, hg * 80, tt * 128, sb + OST_OFF);
        bulk_commit(); bulk_wait0(); fence_async_g();
        red_relaxed(&g_cnt[CNT_O(tt)], 1);
        STAMP(29);
      }
      if (lane == 0) {
#pragma unroll 1
        for (int c = warp == 15 ? 0 : 16 - warp; c < 5; c += (c == 0 ? 1 : 3)) {
          mbar_wait(BAR(B_YDONE + c), 0);
          bulk_st(g_y + (size_t)(128 * c + b) * 2048, sb + CH_OFF + c * CH_SZ + HB_OFF, 4096);
          bulk_commit(); bulk_wait0(); fence_async_g();
          red_relaxed(&g_cnt[CNT_Y(c)], 1);
        }
      }
    }
  }
}

typedef CUresult (*EncFn)(CUtensorMap*, CUtensorMapDataType, cuuint32_t, void*, const cuuint64_t*, const cuuint64_t*, const cuuint32_t*,
                          const cuuint32_t*, CUtensorMapInterleave, CUtensorMapSwizzle, CUtensorMapL2promotion, CUtensorMapFloatOOBfill);

static void enc(EncFn fn, CUtensorMap* m, const void* base, int rank, const cuuint64_t* dims, const cuuint64_t* strides, const cuuint32_t* box,
                CUtensorMapSwizzle sw) {
  cuuint32_t es[3] = {1, 1, 1};
  fn(m, CU_TENSOR_MAP_DATA_TYPE_BFLOAT16, rank, const_cast<void*>(base), dims, strides, box, es, CU_TENSOR_MAP_INTERLEAVE_NONE, sw,
     CU_TENSOR_MAP_L2_PROMOTION_L2_128B, CU_TENSOR_MAP_FLOAT_OOB_FILL_NONE);
}

extern "C" void kernel_launch(void* const* d_in, const int* in_sizes, int n_in, void* d_out, int out_size) {
  static EncFn fn = nullptr;
  static void *o_ptr = nullptr, *xr_ptr = nullptr;
  if (!fn) {
    cudaDriverEntryPointQueryResult qr;
    cudaGetDriverEntryPoint("cuTensorMapEncodeTiled", (void**)&fn, cudaEnableDefault, &qr);
    cudaFuncSetAttribute(fused_kernel, cudaFuncAttributeMaxDynamicSharedMemorySize, SMEM_BYTES);
    cudaGetSymbolAddress(&o_ptr, g_o);
    cudaGetSymbolAddress(&xr_ptr, g_xr);
  }
  Params P;
  P.q = (const bf16*)d_in[0]; P.k = (const bf16*)d_in[1]; P.v = (const bf16*)d_in[2]; P.shift = (const bf16*)d_in[3];
  P.h = (const bf16*)d_in[4]; P.dvec = (const bf16*)d_in[5]; P.x = (const bf16*)d_in[6]; P.wqkv = (const bf16*)d_in[7];
  P.wo = (const bf16*)d_in[8]; P.out = (bf16*)d_out;
  CUtensorMap tmX, tmW64, tmW16, tmWo, tmOld, tmOst, tmOut, tmXr;
  { cuuint64_t d[3] = {640, 2, 1024}, s[2] = {1280, 2560}; cuuint32_t bx[3] = {64, 1, 128}; enc(fn, &tmX, P.x, 3, d, s, bx, CU_TENSOR_MAP_SWIZZLE_128B); }
  { cuuint64_t d[3] = {640, 640, 3}, s[2] = {3840, 1280}; cuuint32_t bx[3] = {64, 32, 3}; enc(fn, &tmW64, P.wqkv, 3, d, s, bx, CU_TENSOR_MAP_SWIZZLE_128B); }
  { cuuint64_t d[3] = {640, 640, 3}, s[2] = {3840, 1280}; cuuint32_t bx[3] = {16, 32, 3}; enc(fn, &tmW16, P.wqkv, 3, d, s, bx, CU_TENSOR_MAP_SWIZZLE_32B); }
  { cuuint64_t d[2] = {640, 640}, s[1] = {1280}; cuuint32_t bx[2] = {32, 32}; enc(fn, &tmWo, P.wo, 2, d, s, bx, CU_TENSOR_MAP_SWIZZLE_64B); }
  { cuuint64_t d[2] = {640, 2048}, s[1] = {1280}; cuuint32_t bx[2] = {64, 128}; enc(fn, &tmOld, o_ptr, 2, d, s, bx, CU_TENSOR_MAP_SWIZZLE_128B); }
  { cuuint64_t d[2] = {640, 2048}, s[1] = {1280}; cuuint32_t bx[2] = {80, 128}; enc(fn, &tmOst, o_ptr, 2, d, s, bx, CU_TENSOR_MAP_SWIZZLE_NONE); }
  { cuuint64_t d[3] = {1280, 2, 1024}, s[2] = {2560, 5120}; cuuint32_t bx[3] = {80, 1, 16}; enc(fn, &tmOut, P.out, 3, d, s, bx, CU_TENSOR_MAP_SWIZZLE_NONE); }
  { cuuint64_t d[2] = {2048, 640}, s[1] = {4096}; cuuint32_t bx[2] = {16, 128}; enc(fn, &tmXr, xr_ptr, 2, d, s, bx, CU_TENSOR_MAP_SWIZZLE_NONE); }
  fused_kernel<<<128, 512, SMEM_BYTES>>>(tmX, tmW64, tmW16, tmWo, tmOld, tmOst, tmOut, tmXr, P);
}
```
